```python
import torch

def _softmax(x, axis=-1):
    return torch.softmax(x, dim=axis)
def _gelu(x):
    return torch.nn.functional.gelu(x, approximate="tanh")
def _silu(x):
    return torch.nn.functional.silu(x)
def _sigmoid(x):
    return torch.sigmoid(x)
def _layernorm(x, axis=-1, eps=1e-5):
    m = x.mean(dim=axis, keepdim=True)
    v = x.var(dim=axis, keepdim=True, unbiased=False)
    return (x - m) / torch.sqrt(v + eps)
def _scatter_add(tgt, idx, src, axis=0):
    return tgt.clone().index_add_(axis, idx, src)
def _segment_sum(src, seg, n):
    out = torch.zeros((n,) + src.shape[1:], dtype=src.dtype)
    return out.index_add_(0, seg, src)
def _pad(x, pw):
    flat = tuple(v for pair in reversed(pw) for v in pair)
    return torch.nn.functional.pad(x, flat)

kernel_name = 'recurrent_scan__gqa_block_cached__swiglu_ffn__decode'

def setup_inputs():

    _w = (lambda a: (lambda t: t.to(torch.bfloat16) if t.is_floating_point() else t)(torch.as_tensor(a)))
    def _A_setup():
        B, Sq, D = 8, 1, 576
        Hq, Hkv, Sk, Dh = 32, 16, 8192, 128
        assert Hq % Hkv == 0, (Hq, Hkv)
        return {
            "x": _w((lambda *s: torch.randn(*s, dtype=torch.bfloat16) * 0.05)(B, Sq, D)),
            "k_cache": _w((lambda *s: torch.randn(*s, dtype=torch.bfloat16) * 0.8)(B, Hkv, Sk, Dh)),
            "v_cache": _w((lambda *s: torch.randn(*s, dtype=torch.bfloat16) * 0.2)(B, Hkv, Sk, Dh)),
            "wq": _w((lambda *s: torch.randn(*s, dtype=torch.bfloat16) * 0.8)(D, Hq * Dh) * (D ** -0.5)),
            "wo": _w((lambda *s: torch.randn(*s, dtype=torch.bfloat16) * 0.2)(Hq * Dh, D) * ((Hq * Dh) ** -0.5)),
        }
    _A_in = _A_setup()

    def _B_setup():
        B, S, D, F = 8, 1, 576, 4608
        return {
            "x": _w((lambda *s: torch.randn(*s, dtype=torch.bfloat16) * 0.05)(B, S, D)),
            "w_gate": _w((lambda *s: torch.randn(*s, dtype=torch.bfloat16) * 0.1)(D, F)),
            "w_up": _w((lambda *s: torch.randn(*s, dtype=torch.bfloat16) * 0.1)(D, F)),
            "w_down": _w((lambda *s: torch.randn(*s, dtype=torch.bfloat16) * 0.1)(F, D)),
        }
    _B_in = _B_setup()

    return {
        "A_x": _A_in["x"],
        "A_k_cache": _A_in["k_cache"],
        "A_v_cache": _A_in["v_cache"],
        "A_wq": _A_in["wq"],
        "A_wo": _A_in["wo"],
        "B_x": _B_in["x"],
        "B_w_gate": _B_in["w_gate"],
        "B_w_up": _B_in["w_up"],
        "B_w_down": _B_in["w_down"],
    }

def reference(A_x, A_k_cache, A_v_cache, A_wq, A_wo, B_x, B_w_gate, B_w_up, B_w_down):
    def _A_ref(x, k_cache, v_cache, wq, wo):
        B, Sq, D = x.shape
        Hq, Dh = 32, 128
        Hkv = k_cache.shape[1]
        rep = Hq // Hkv
        q = (lambda x, *d: x.permute(*d))((x @ wq).reshape(B, Sq, Hq, Dh), 0, 2, 1, 3)
        k = (lambda x, n, axis: torch.repeat_interleave(x, n, dim=axis))(k_cache, rep, axis=1)
        v = (lambda x, n, axis: torch.repeat_interleave(x, n, dim=axis))(v_cache, rep, axis=1)
        scores = torch.einsum("bhqd,bhkd->bhqk", q, k) * (Dh ** -0.5)
        p = _softmax(scores, axis=-1)
        o = torch.einsum("bhqk,bhkd->bhqd", p, v)
        return (lambda x, *d: x.permute(*d))(o, 0, 2, 1, 3).reshape(B, Sq, Hq * Dh) @ wo

    def _B_ref(x, w_gate, w_up, w_down):
        g = _silu(x @ w_gate)
        u = x @ w_up
        return (g * u) @ w_down

    x = A_x
    xn = _layernorm(x, axis=-1)
    s = _A_ref(xn, A_k_cache, A_v_cache, A_wq, A_wo)
    g = _silu(_B_ref(xn, B_w_gate, B_w_up, B_w_down))
    return x + s * g
```

```cpp
#include <cuda_runtime.h>
#include <cuda_bf16.h>
#include <cuda.h>
#include <stdint.h>

namespace {

constexpr int NB = 8, DM = 576, HKV = 16, SK = 8192, DH = 128, FF = 4608;
constexpr int NPAIR = NB * HKV;
constexpr int TILE = 64;
constexpr int TPP = SK / TILE;
constexpr int NKV = NPAIR * TPP;
constexpr int NCTA = 132;
constexpr int NST = 4;
constexpr int STAGE = 36864;
constexpr int NUNIT = FF / 32;
constexpr int NEARLY = NUNIT - NCTA;
constexpr int NSTATIC = (NCTA - NEARLY) * NST + NEARLY;
constexpr int XP = 584;
constexpr int NTHREADS = 288;

#define INFLIGHT 2
#define LATECLAIM 400
#define KV_ORDER 1

constexpr int SM_STAGES = 0;
constexpr int SM_WBUF = NST * STAGE;
constexpr int SM_XN = SM_WBUF + STAGE;
constexpr int SM_GU = SM_XN + NB * XP * 2;
constexpr int SM_RED = SM_GU + 2 * 8 * 36 * 4;
constexpr int SM_RED2 = SM_RED + 14 * 36 * 4;
constexpr int SM_PART = SM_RED2 + 14 * 36 * 4;
constexpr int SM_SSUM = SM_PART + 2 * 4 * 40 * 4;
constexpr int SM_BAR = SM_SSUM + 36 * 4;
constexpr int NBAR = 3 * NST + 2 + 6 + 2;
constexpr int SM_DESC = SM_BAR + NBAR * 8;
constexpr int SM_TOTAL = SM_DESC + 64;
constexpr int SMEM_BYTES = SM_TOTAL + 1024;

struct Maps { CUtensorMap k, v, wq, wg, wu, wo, wd; };

__device__ __align__(128) unsigned g_queue[32];
__device__ __align__(128) unsigned g_state[32];
__device__ __align__(128) uint32_t g_q[NPAIR * 256];
__device__ __align__(128) float2 g_ml[NPAIR * 2 * TPP];
__device__ __align__(128) uint2 g_po[NPAIR * 2 * 4 * TPP * 8];
__device__ __align__(128) float4 g_sp[128 * NB * (DM / 4)];
__device__ __align__(128) float4 g_fp[NUNIT * NB * (DM / 4)];
#define TRB 7
#define TRACE(i) do {} while (0)

__device__ __forceinline__ uint32_t s2u(const void* p) { return (uint32_t)__cvta_generic_to_shared(p); }
__device__ __forceinline__ void mbar_init(uint32_t b, int c) { asm volatile("mbarrier.init.shared::cta.b64 [%0], %1;" :: "r"(b), "r"(c)); }
__device__ __forceinline__ void mbar_expect(uint32_t b, uint32_t bytes) { asm volatile("mbarrier.arrive.expect_tx.shared::cta.b64 _, [%0], %1;" :: "r"(b), "r"(bytes) : "memory"); }
__device__ __forceinline__ void mbar_arrive(uint32_t b) { asm volatile("mbarrier.arrive.shared::cta.b64 _, [%0];" :: "r"(b) : "memory"); }
__device__ __forceinline__ bool mbar_try(uint32_t b, uint32_t ph) {
    uint32_t ok;
    asm volatile("{\n.reg .pred p;\nmbarrier.try_wait.parity.shared::cta.b64 p, [%1], %2;\nselp.u32 %0, 1, 0, p;\n}" : "=r"(ok) : "r"(b), "r"(ph) : "memory");
    return ok != 0;
}
constexpr long long SPIN_LIMIT = 4000000000LL;
__device__ __forceinline__ void mbar_wait(uint32_t b, uint32_t ph) {
    if (mbar_try(b, ph)) return;
    long long t0 = clock64();
    while (!mbar_try(b, ph)) { if (clock64() - t0 > SPIN_LIMIT) __trap(); }
}
struct Spin {
    long long t0 = 0;
    __device__ __forceinline__ void tick() { long long t = clock64(); if (t0 == 0) t0 = t; else if (t - t0 > SPIN_LIMIT) __trap(); }
};
__device__ __forceinline__ void bulk_g2s(uint32_t dst, const void* src, uint32_t bytes, uint32_t bar) {
    asm volatile("cp.async.bulk.shared::cluster.global.mbarrier::complete_tx::bytes [%0], [%1], %2, [%3];" :: "r"(dst), "l"(src), "r"(bytes), "r"(bar) : "memory");
}
__device__ __forceinline__ void tma2d(uint32_t dst, const CUtensorMap* m, int c0, int c1, uint32_t bar) {
    asm volatile("cp.async.bulk.tensor.2d.shared::cluster.global.mbarrier::complete_tx::bytes [%0], [%1, {%3, %4}], [%2];" :: "r"(dst), "l"(m), "r"(bar), "r"(c0), "r"(c1) : "memory");
}
__device__ __forceinline__ void tma3d(uint32_t dst, const CUtensorMap* m, int c0, int c1, int c2, uint32_t bar, uint64_t pol) {
    asm volatile("cp.async.bulk.tensor.3d.shared::cluster.global.mbarrier::complete_tx::bytes.L2::cache_hint [%0], [%1, {%3, %4, %5}], [%2], %6;" :: "r"(dst), "l"(m), "r"(bar), "r"(c0), "r"(c1), "r"(c2), "l"(pol) : "memory");
}
__device__ __forceinline__ void ldsm4(uint32_t (&r)[4], uint32_t a) {
    asm volatile("ldmatrix.sync.aligned.m8n8.x4.shared.b16 {%0,%1,%2,%3}, [%4];" : "=r"(r[0]), "=r"(r[1]), "=r"(r[2]), "=r"(r[3]) : "r"(a));
}
__device__ __forceinline__ void ldsm4t(uint32_t (&r)[4], uint32_t a) {
    asm volatile("ldmatrix.sync.aligned.m8n8.x4.trans.shared.b16 {%0,%1,%2,%3}, [%4];" : "=r"(r[0]), "=r"(r[1]), "=r"(r[2]), "=r"(r[3]) : "r"(a));
}
__device__ __forceinline__ void mma16816(float (&c)[4], const uint32_t (&a)[4], uint32_t b0, uint32_t b1) {
    asm("mma.sync.aligned.m16n8k16.row.col.f32.bf16.bf16.f32 {%0,%1,%2,%3}, {%4,%5,%6,%7}, {%8,%9}, {%0,%1,%2,%3};"
                 : "+f"(c[0]), "+f"(c[1]), "+f"(c[2]), "+f"(c[3]) : "r"(a[0]), "r"(a[1]), "r"(a[2]), "r"(a[3]), "r"(b0), "r"(b1));
}
__device__ __forceinline__ uint4 ld_relaxed4(const void* p) {
    uint4 v; asm volatile("ld.relaxed.gpu.global.v4.u32 {%0,%1,%2,%3}, [%4];" : "=r"(v.x), "=r"(v.y), "=r"(v.z), "=r"(v.w) : "l"(p) : "memory"); return v;
}
__device__ __forceinline__ uint2 ld_relaxed2(const void* p) {
    uint2 v; asm volatile("ld.relaxed.gpu.global.v2.u32 {%0,%1}, [%2];" : "=r"(v.x), "=r"(v.y) : "l"(p) : "memory"); return v;
}
__device__ __forceinline__ uint32_t ld_relaxed1(const void* p) {
    uint32_t v; asm volatile("ld.relaxed.gpu.global.u32 %0, [%1];" : "=r"(v) : "l"(p) : "memory"); return v;
}
__device__ __forceinline__ uint32_t ld_acquire1(const void* p) {
    uint32_t v; asm volatile("ld.acquire.gpu.global.u32 %0, [%1];" : "=r"(v) : "l"(p) : "memory"); return v;
}
__device__ __forceinline__ void st_relaxed4(void* p, uint32_t a, uint32_t b, uint32_t c, uint32_t d) {
    asm volatile("st.relaxed.gpu.global.v4.u32 [%0], {%1,%2,%3,%4};" :: "l"(p), "r"(a), "r"(b), "r"(c), "r"(d) : "memory");
}
__device__ __forceinline__ void st_relaxed1(void* p, uint32_t a) {
    asm volatile("st.relaxed.gpu.global.u32 [%0], %1;" :: "l"(p), "r"(a) : "memory");
}
__device__ __forceinline__ void st_relaxed2(void* p, uint32_t a, uint32_t b) {
    asm volatile("st.relaxed.gpu.global.v2.u32 [%0], {%1,%2};" :: "l"(p), "r"(a), "r"(b) : "memory");
}
__device__ __forceinline__ uint32_t lds32(uint32_t a) { uint32_t v; asm volatile("ld.shared.u32 %0, [%1];" : "=r"(v) : "r"(a) : "memory"); return v; }
__device__ __forceinline__ uint4 lds128(uint32_t a) { uint4 v; asm volatile("ld.shared.v4.u32 {%0,%1,%2,%3}, [%4];" : "=r"(v.x), "=r"(v.y), "=r"(v.z), "=r"(v.w) : "r"(a) : "memory"); return v; }
__device__ __forceinline__ void bar_cons() { asm volatile("bar.sync 1, 128;" ::: "memory"); }
__device__ __forceinline__ void bar_comb() { asm volatile("bar.sync 2, 128;" ::: "memory"); }
__device__ __forceinline__ float bfr(float v) { return __bfloat162float(__float2bfloat16_rn(v)); }
__device__ __forceinline__ uint32_t pack_bf16(float lo, float hi) {
    uint32_t r; asm("cvt.rn.bf16x2.f32 %0, %1, %2;" : "=r"(r) : "f"(hi), "f"(lo)); return r;
}
__device__ __forceinline__ float ex2(float x) { float y; asm("ex2.approx.ftz.f32 %0, %1;" : "=f"(y) : "f"(x)); return y; }
__device__ __forceinline__ float silu_f(float v) { return v / (1.0f + __expf(-v)); }
__device__ __forceinline__ uint32_t tagf(float v, uint32_t tag) { return (__float_as_uint(v) & ~1u) | tag; }
__device__ __forceinline__ float untagf(uint32_t w) { return __uint_as_float(w & ~1u); }
__device__ __forceinline__ uint32_t pack_tag(float lo, float hi, uint32_t tag) {
    uint32_t l = ((__float_as_uint(lo) + 0x10000u) >> 16) & 0xFFFEu;
    uint32_t h = pack_bf16(0.f, hi) & 0xFFFF0000u;
    return h | l | tag;
}

__device__ __forceinline__ uint32_t addr_w32(uint32_t base, int lane, int mt, int ks) {
    int mat = lane >> 3, row = ks * 16 + (mat >> 1) * 8 + (lane & 7), c = mt * 2 + (mat & 1);
    return base + row * 64 + ((c ^ ((row >> 1) & 3)) << 4);
}
__device__ __forceinline__ uint32_t addr_w576(uint32_t base, int lane, int mt, int ks) {
    int mat = lane >> 3, row = ks * 16 + (mat >> 1) * 8 + (lane & 7), cc = mt * 2 + (mat & 1);
    int line = row * 9 + (cc >> 3);
    return base + line * 128 + (((cc & 7) ^ (line & 7)) << 4);
}
__device__ __forceinline__ uint32_t addr_kv(uint32_t base, int key, int chunk) {
    int line = key * 2 + (chunk >> 3);
    return base + line * 128 + (((chunk & 7) ^ (line & 7)) << 4);
}

template <int NKS>
__device__ __forceinline__ void proj32(float (&acc)[4], uint32_t wbase, uint32_t xn, int lane, int mt, int ks0) {
    float a0[4] = {0.f, 0.f, 0.f, 0.f}, a1[4] = {0.f, 0.f, 0.f, 0.f};
    const int g = lane >> 2, t = lane & 3;
    const uint32_t xb = xn + (g * XP + 2 * t) * 2;
#pragma unroll
    for (int i = 0; i < NKS; i++) {
        int ks = ks0 + i;
        uint32_t a[4];
        ldsm4t(a, addr_w32(wbase, lane, mt, ks));
        uint32_t b0 = lds32(xb + ks * 32), b1 = lds32(xb + ks * 32 + 16);
        if (i & 1) mma16816(a1, a, b0, b1); else mma16816(a0, a, b0, b1);
    }
#pragma unroll
    for (int i = 0; i < 4; i++) acc[i] = a0[i] + a1[i];
}

__device__ __forceinline__ void ffn_unit(uint32_t sb, uint32_t bufG, uint32_t bufU, uint32_t bufD, uint32_t barG, uint32_t barU,
                                         uint32_t barD, int unit, int warp, int lane, uint32_t tag) {
    const int g = lane >> 2, t = lane & 3;
    const int mat = warp >> 1, mt = warp & 1;
    mbar_wait(mat ? barU : barG, 0);
    float acc[4];
    proj32<36>(acc, mat ? bufU : bufG, sb + SM_XN, lane, mt, 0);
    float* gu = reinterpret_cast<float*>(__cvta_shared_to_generic(sb + SM_GU));
    gu[(mat * 8 + 2 * t) * 36 + mt * 16 + g] = acc[0];
    gu[(mat * 8 + 2 * t + 1) * 36 + mt * 16 + g] = acc[1];
    gu[(mat * 8 + 2 * t) * 36 + mt * 16 + g + 8] = acc[2];
    gu[(mat * 8 + 2 * t + 1) * 36 + mt * 16 + g + 8] = acc[3];
    bar_cons();
    uint32_t hb[4];
#pragma unroll
    for (int j = 0; j < 4; j++) {
        int f = j * 8 + 2 * t;
        float2 gg = *reinterpret_cast<const float2*>(gu + g * 36 + f);
        float2 uu = *reinterpret_cast<const float2*>(gu + (8 + g) * 36 + f);
        float h0 = bfr(silu_f(bfr(gg.x))) * bfr(uu.x), h1 = bfr(silu_f(bfr(gg.y))) * bfr(uu.y);
        hb[j] = pack_bf16(h0, h1);
    }
    mbar_wait(barD, 0);
    const int u0 = warp < 2 ? warp * 5 : 10 + (warp - 2) * 4, nu = warp < 2 ? 5 : 4;
    float c0[5][4], c1[5][4];
#pragma unroll
    for (int i = 0; i < 5; i++) {
        const int u = min(u0 + i, 17);
#pragma unroll
        for (int k = 0; k < 4; k++) { c0[i][k] = 0.f; c1[i][k] = 0.f; }
#pragma unroll
        for (int ks = 0; ks < 2; ks++) {
            uint32_t a[4];
            ldsm4t(a, addr_w576(bufD, lane, 2 * u, ks));     mma16816(c0[i], a, hb[2 * ks], hb[2 * ks + 1]);
            ldsm4t(a, addr_w576(bufD, lane, 2 * u + 1, ks)); mma16816(c1[i], a, hb[2 * ks], hb[2 * ks + 1]);
        }
    }
#pragma unroll
    for (int i = 0; i < 5; i++) {
        if (i < nu) {
            float4* dst = g_fp + ((size_t)unit * NB + 2 * t) * (DM / 4) + (u0 + i) * 8 + g;
            st_relaxed4(dst, tagf(c0[i][0], tag), tagf(c0[i][2], tag), tagf(c1[i][0], tag), tagf(c1[i][2], tag));
            st_relaxed4(dst + DM / 4, tagf(c0[i][1], tag), tagf(c0[i][3], tag), tagf(c1[i][1], tag), tagf(c1[i][3], tag));
        }
    }
}

template <int NROWS, int SLEEP>
__device__ __forceinline__ void gather36(const float4* base, float* red, int tid, uint32_t tag) {
    constexpr int N = (NROWS + 13) / 14;
    if (tid < 126) {
        const int f = tid % 9, r0 = tid / 9;
        const float4* src = base + (size_t)r0 * NB * (DM / 4) + f;
        uint4 v[N];
        uint32_t pend = (r0 + 14 * (N - 1) < NROWS) ? (1u << N) - 1u : (1u << (N - 1)) - 1u;
        v[N - 1] = make_uint4(0, 0, 0, 0);
        Spin sp;
        while (true) {
#pragma unroll
            for (int i = 0; i < N; i++)
                if (pend >> i & 1) v[i] = ld_relaxed4(src + (size_t)i * 14 * NB * (DM / 4));
#pragma unroll
            for (int i = 0; i < N; i++)
                if ((pend >> i & 1) && (((v[i].x ^ tag) | (v[i].y ^ tag) | (v[i].z ^ tag) | (v[i].w ^ tag)) & 1u) == 0) pend &= ~(1u << i);
            if (!pend) break;
            if (SLEEP) __nanosleep(SLEEP);
            sp.tick();
        }
        float a0 = 0.f, a1 = 0.f, a2 = 0.f, a3 = 0.f;
#pragma unroll
        for (int i = 0; i < N; i++) { a0 += untagf(v[i].x); a1 += untagf(v[i].y); a2 += untagf(v[i].z); a3 += untagf(v[i].w); }
        *reinterpret_cast<float4*>(red + r0 * 36 + f * 4) = make_float4(a0, a1, a2, a3);
    }
}

__device__ __forceinline__ void issue_w32(uint32_t dst, const CUtensorMap* m, int col, uint32_t bar) {
    mbar_expect(bar, STAGE);
    tma2d(dst, m, col, 0, bar);
    tma2d(dst + 12288, m, col, 192, bar);
    tma2d(dst + 24576, m, col, 384, bar);
}

__global__ void __launch_bounds__(NTHREADS, 1)
fused_decode_kernel(const __grid_constant__ Maps maps, const __nv_bfloat16* __restrict__ x, __nv_bfloat16* __restrict__ out) {
    extern __shared__ uint8_t smem_raw[];
    const uint32_t sb = (s2u(smem_raw) + 1023u) & ~1023u;
    uint8_t* sg = smem_raw + (sb - s2u(smem_raw));
    const int tid = threadIdx.x, warp = tid >> 5, lane = tid & 31, cta = blockIdx.x;
    const uint32_t bar_full = sb + SM_BAR, bar_empty = bar_full + NST * 8;
    const uint32_t bar_q = bar_empty + NST * 8;
    const uint32_t bar_wq = bar_q + NST * 8, bar_wo = bar_wq + 8;
    const uint32_t bar_fin = bar_wo + 8;
    const uint32_t bar_wfree = bar_fin + 48, bar_ssum = bar_wfree + 8;
    volatile int* desc = reinterpret_cast<volatile int*>(sg + SM_DESC);

    if (tid < 7) asm volatile("prefetch.tensormap [%0];" :: "l"(reinterpret_cast<const CUtensorMap*>(&maps) + tid) : "memory");

    if (warp == NST) {
        uint64_t pol; asm volatile("createpolicy.fractional.L2::evict_first.b64 %0, 1.0;" : "=l"(pol));
        auto issue_kv = [&](int tile, int st) {
            const uint32_t bar = bar_full + st * 8, dst = sb + st * STAGE;
            desc[st] = tile;
            mbar_expect(bar, 2 * 16384);
            tma3d(dst, &maps.k, 0, 0, tile * TILE, bar, pol);
            tma3d(dst + 16384, &maps.v, 0, 0, tile * TILE, bar, pol);
        };
        auto issue_d = [&](int unit, uint32_t dst, uint32_t bar) {
            mbar_expect(bar, STAGE);
            tma3d(dst, &maps.wd, 0, 0, unit * 32, bar, pol);
        };
        uint32_t fifo[INFLIGHT];
#pragma unroll
        for (int i = 0; i < INFLIGHT; i++) fifo[i] = 0;
        auto gate = [&]() { if (fifo[0]) mbar_wait(fifo[0] & ~1u, fifo[0] & 1u); };
        auto push = [&](uint32_t bar, uint32_t par) {
#pragma unroll
            for (int i = 0; i + 1 < INFLIGHT; i++) fifo[i] = fifo[i + 1];
            fifo[INFLIGHT - 1] = bar | par;
        };
        const bool early = cta < NEARLY;
        const int first0 = early ? (NCTA - NEARLY) * NST + cta : cta - NEARLY;
        auto prologue = [&](int i) {
            if (early) {
                const int unit = NCTA + cta;
                if (i == 0) { issue_w32(sb + 0 * STAGE, &maps.wg, unit * 32, bar_fin + 0); push(bar_fin + 0, 0); }
                if (i == 1) { issue_w32(sb + 1 * STAGE, &maps.wu, unit * 32, bar_fin + 8); push(bar_fin + 8, 0); }
                if (i == 2) { issue_d(unit, sb + 2 * STAGE, bar_fin + 16); push(bar_fin + 16, 0); }
                if (i == 3) { issue_kv(first0, 3); push(bar_full + 24, 0); }
            } else {
                issue_kv(first0 + i * (NCTA - NEARLY), i); push(bar_full + i * 8, 0);
            }
        };
        int next = 0;
        if (lane == 0) {
            TRACE(0);
            for (int i = 0; i < NST; i++) { mbar_init(bar_full + i * 8, 1); mbar_init(bar_empty + i * 8, 1); mbar_init(bar_q + i * 8, 1); }
            mbar_init(bar_wq, 1); mbar_init(bar_wo, 1);
            for (int i = 0; i < 6; i++) mbar_init(bar_fin + i * 8, 1);
            mbar_init(bar_wfree, NST); mbar_init(bar_ssum, 36);
            asm volatile("fence.mbarrier_init.release.cluster;" ::: "memory");
            if (cta < 128) { issue_w32(sb + SM_WBUF, &maps.wq, cta * 32, bar_wq); push(bar_wq, 0); }
#pragma unroll
            for (int i = 0; i < INFLIGHT - 1; i++) prologue(i);
            next = (int)atomicAdd(&g_queue[0], 1u) + NSTATIC;
        }
        __syncwarp();
        __syncthreads();
        if (lane == 0) {
#pragma unroll
            for (int i = INFLIGHT - 1; i < NST; i++) { gate(); prologue(i); }
            if (early) mbar_wait(bar_q + 24, 0);
            int st = 0; uint32_t ph = 0;
            while (true) {
                gate();
                mbar_wait(bar_empty + st * 8, ph);
                if (next < 0) next = (int)atomicAdd(&g_queue[0], 1u) + NSTATIC;
                if (next >= NKV) break;
                issue_kv(next, st);
                push(bar_full + st * 8, (early && st < 3) ? ph : ph ^ 1u);
                mbar_expect(bar_q + st * 8, 1024);
                bulk_g2s(sb + st * STAGE + 32768, g_q + (next / TPP) * 256, 1024, bar_q + st * 8);
                next = next >= NKV - LATECLAIM ? -1 : (int)atomicAdd(&g_queue[0], 1u) + NSTATIC;
                if (++st == NST) { st = 0; ph ^= 1; }
            }
            TRACE(3);
#pragma unroll
            for (int i = 0; i < NST; i++) {
                if (i < 3) gate();
                mbar_wait(bar_empty + st * 8, ph);
                const uint32_t dst = sb + st * STAGE;
                if (i < 3) desc[4 + i] = st;
                if (i == 0) issue_w32(dst, &maps.wg, cta * 32, bar_fin + 24);
                if (i == 1) issue_w32(dst, &maps.wu, cta * 32, bar_fin + 32);
                if (i == 2) issue_d(cta, dst, bar_fin + 40);
                if (i < 3) push(bar_fin + 24 + i * 8, 0);
                desc[st] = -1;
                mbar_arrive(bar_full + st * 8);
                if (++st == NST) { st = 0; ph ^= 1; }
            }
            if (atomicAdd(&g_state[0], 1u) == NCTA - 1) {
                g_queue[0] = 0; g_state[0] = 0;
                g_state[1] = g_state[1] + 1;
            }
        }
    } else if (warp < NST) {
        const int g = lane >> 2, t = lane & 3;
        float xfin = 0.f;
        if (tid < 36 && cta < 128) {
            int pos = (cta & 15) * 36 + tid;
            int col = (pos >> 5) * 32 + ((pos & 3) >> 1) * 16 + (pos & 1) * 8 + ((pos & 31) >> 2);
            xfin = __bfloat162float(x[(7 - (cta >> 4)) * DM + col]);
        }
        {
            uint32_t xr[2][9];
#pragma unroll
            for (int r = 0; r < 2; r++)
#pragma unroll
                for (int i = 0; i < 9; i++)
                    xr[r][i] = __ldg(reinterpret_cast<const uint32_t*>(x + (warp * 2 + r) * DM) + i * 32 + lane);
#pragma unroll
            for (int r = 0; r < 2; r++) {
                float v[18], s = 0.f;
#pragma unroll
                for (int i = 0; i < 9; i++) { v[2 * i] = __uint_as_float(xr[r][i] << 16); v[2 * i + 1] = __uint_as_float(xr[r][i] & 0xFFFF0000u); s += v[2 * i] + v[2 * i + 1]; }
#pragma unroll
                for (int o = 16; o; o >>= 1) s += __shfl_xor_sync(~0u, s, o);
                const float mean = s * (1.0f / DM);
                float q = 0.f;
#pragma unroll
                for (int i = 0; i < 18; i++) { float d = v[i] - mean; q += d * d; }
#pragma unroll
                for (int o = 16; o; o >>= 1) q += __shfl_xor_sync(~0u, q, o);
                const float mb = bfr(mean), rden = __frcp_rn(bfr(__fsqrt_rn(bfr(bfr(q * (1.0f / DM)) + 1e-5f))));
                uint32_t* xn = reinterpret_cast<uint32_t*>(sg + SM_XN) + (warp * 2 + r) * (XP / 2);
#pragma unroll
                for (int i = 0; i < 9; i++) xn[i * 32 + lane] = pack_bf16(bfr(v[2 * i] - mb) * rden, bfr(v[2 * i + 1] - mb) * rden);
            }
        }
        if (tid == 0) TRACE(14);
        __syncthreads();
        const uint32_t tag = (uint32_t)desc[8];
        if (cta < 128) {
            mbar_wait(bar_wq, 0);
            if (tid == 0) TRACE(15);
            float acc[4];
            const int mt = warp & 1, kh = warp >> 1;
            proj32<18>(acc, sb + SM_WBUF, sb + SM_XN, lane, mt, kh * 18);
            __syncwarp();
            if (lane == 0) mbar_arrive(bar_wfree);
            float* gu = reinterpret_cast<float*>(sg + SM_GU);
            gu[(kh * 8 + 2 * t) * 36 + mt * 16 + g] = acc[0];
            gu[(kh * 8 + 2 * t + 1) * 36 + mt * 16 + g] = acc[1];
            gu[(kh * 8 + 2 * t) * 36 + mt * 16 + g + 8] = acc[2];
            gu[(kh * 8 + 2 * t + 1) * 36 + mt * 16 + g + 8] = acc[3];
            bar_cons();
            {
                const int b = tid >> 4, c = (tid & 15) * 2;
                const float q0 = gu[b * 36 + c] + gu[(8 + b) * 36 + c], q1 = gu[b * 36 + c + 1] + gu[(8 + b) * 36 + c + 1];
                const int hq = cta >> 2, d = (cta & 3) * 32 + c;
                const int off = (b * HKV + (hq >> 1)) * 256 + (hq & 1) * 128 + (d >> 4) * 16 + ((d & 7) >> 1) * 4 + ((d >> 3) & 1) * 2;
                const uint32_t pk = pack_bf16(q0, q1);
                st_relaxed2(g_q + off, (pk << 16) | tag, (pk & 0xFFFF0000u) | tag);
            }
            if (tid == 0) TRACE(1);
            bar_cons();
        }
        if (cta < NEARLY) {
            ffn_unit(sb, sb, sb + STAGE, sb + 2 * STAGE, bar_fin, bar_fin + 8, bar_fin + 16, NCTA + cta, warp, lane, tag);
            bar_cons();
            if (warp < 3 && lane == 0) mbar_arrive(bar_empty + warp * 8);
        }
        const uint32_t kb = sb + warp * STAGE, vb = kb + 16384, qb = kb + 32768;
        const int mat = lane >> 3, r8 = lane & 7;
        const int kkey = (mat & 1) ? 8 + ((r8 + 4) & 7) : r8;
        const int rho = (r8 >> 1) + (mat >> 1) * 4;
        const int vkey = (r8 & 1) ? 8 + ((rho + 4) & 7) : rho;
        const float sc = 0.08838834764831845f * 1.4426950408889634f;
        uint32_t ph = 0;
        while (true) {
            mbar_wait(bar_full + warp * 8, ph);
            ph ^= 1;
            const int tile = desc[warp];
            if (tile < 0) break;
            mbar_wait(bar_q + warp * 8, ph ^ 1u);
            uint32_t qf[16];
            {
                const bool on = (g == 0) || (g == 2);
                uint4 v[8];
                uint32_t bad = 0;
#pragma unroll
                for (int j = 0; j < 8; j++) {
                    v[j] = make_uint4(tag, tag, tag, tag);
                    if (on) v[j] = lds128(qb + (g >> 1) * 512 + j * 64 + t * 16);
                    bad |= (v[j].x ^ tag) | (v[j].y ^ tag) | (v[j].z ^ tag) | (v[j].w ^ tag);
                }
                if (bad & 1u) {
                    Spin sp;
                    do {
                        bad = 0;
#pragma unroll
                        for (int j = 0; j < 8; j++) {
                            v[j] = ld_relaxed4(g_q + (tile / TPP) * 256 + (g >> 1) * 128 + j * 16 + t * 4);
                            bad |= (v[j].x ^ tag) | (v[j].y ^ tag) | (v[j].z ^ tag) | (v[j].w ^ tag);
                        }
                        sp.tick();
                    } while (bad & 1u);
                }
                __syncwarp();
#pragma unroll
                for (int j = 0; j < 8; j++) { qf[2 * j] = __byte_perm(v[j].x, v[j].y, 0x7632); qf[2 * j + 1] = __byte_perm(v[j].z, v[j].w, 0x7632); }
            }
            float s[4][4];
#pragma unroll
            for (int mt = 0; mt < 4; mt++) { s[mt][0] = s[mt][1] = s[mt][2] = s[mt][3] = 0.f; }
#pragma unroll
            for (int ks = 0; ks < 8; ks++)
#pragma unroll
                for (int mt = 0; mt < 4; mt++) {
                    uint32_t a[4];
                    ldsm4(a, addr_kv(kb, mt * 16 + kkey, 2 * ks + (mat >> 1)));
                    mma16816(s[mt], a, qf[2 * ks], qf[2 * ks + 1]);
                }
            float m = fmaxf(fmaxf(fmaxf(s[0][0], s[0][2]), fmaxf(s[1][0], s[1][2])), fmaxf(fmaxf(s[2][0], s[2][2]), fmaxf(s[3][0], s[3][2])));
            m = fmaxf(m, __shfl_xor_sync(~0u, m, 4));
            m = fmaxf(m, __shfl_xor_sync(~0u, m, 8));
            m = fmaxf(m, __shfl_xor_sync(~0u, m, 16));
            const float ms = untagf(__float_as_uint(m * sc));
            float l = 0.f;
            uint32_t pb[4][2];
#pragma unroll
            for (int mt = 0; mt < 4; mt++) {
                const float p0 = ex2(fmaf(s[mt][0], sc, -ms)), p1 = ex2(fmaf(s[mt][2], sc, -ms));
                l += p0 + p1;
                const uint32_t pk = pack_bf16(p0, p1);
                pb[mt][0] = __shfl_sync(~0u, pk, 4 * t + (g & 1));
                pb[mt][1] = __shfl_sync(~0u, pk, 4 * (t + 4) + (g & 1));
            }
            l += __shfl_xor_sync(~0u, l, 4);
            l += __shfl_xor_sync(~0u, l, 8);
            l += __shfl_xor_sync(~0u, l, 16);
            float o[8][4];
#pragma unroll
            for (int i = 0; i < 8; i++) { o[i][0] = o[i][1] = o[i][2] = o[i][3] = 0.f; }
#pragma unroll
            for (int kk = 0; kk < 4; kk++)
#pragma unroll
                for (int i = 0; i < 8; i++) {
                    uint32_t a[4];
                    ldsm4t(a, addr_kv(vb, kk * 16 + vkey, 2 * i + (mat & 1)));
                    mma16816(o[i], a, pb[kk][0], pb[kk][1]);
                }
            __syncwarp();
            if (lane == 0) mbar_arrive(bar_empty + warp * 8);
            const float inv = 1.0f / l;
            const float inv1 = __shfl_down_sync(~0u, inv, 1);
            const int pair = tile / TPP, tt = tile % TPP;
            if (t == 0) {
                uint2* dst = g_po + ((size_t)pair * 8 * TPP + tt) * 8 + g;
#pragma unroll
                for (int qd = 0; qd < 4; qd++) {
                    st_relaxed2(dst + (size_t)qd * TPP * 8,
                                pack_tag(o[2 * qd][0] * inv, o[2 * qd][2] * inv, tag), pack_tag(o[2 * qd + 1][0] * inv, o[2 * qd + 1][2] * inv, tag));
                    st_relaxed2(dst + (size_t)(4 + qd) * TPP * 8,
                                pack_tag(o[2 * qd][1] * inv1, o[2 * qd][3] * inv1, tag), pack_tag(o[2 * qd + 1][1] * inv1, o[2 * qd + 1][3] * inv1, tag));
                }
            }
            if (lane < 2) st_relaxed2(g_ml + (pair * 2 + lane) * TPP + tt, tagf(ms, tag), tagf(l, tag));
        }
        if (tid == 0) TRACE(4);
        {
            const int u0 = warp < 2 ? warp * 5 : 10 + (warp - 2) * 4, nu = warp < 2 ? 5 : 4;
            const uint32_t inv = tag ^ 1u;
            for (int i = 0; i < nu; i++) {
                float4* dst = g_fp + ((size_t)cta * NB + 2 * t) * (DM / 4) + (u0 + i) * 8 + g;
                st_relaxed4(dst, inv, inv, inv, inv);
                st_relaxed4(dst + DM / 4, inv, inv, inv, inv);
            }
        }
        {
            mbar_wait(bar_fin + 24 + (warp >> 1) * 8, 0);
            const uint32_t bufGU = sb + desc[4 + (warp >> 1)] * STAGE;
            const int stG = (desc[4 + (warp >> 1)] + NST - (warp >> 1)) % NST;
            const uint32_t bufD = sb + ((stG + 2) % NST) * STAGE;
            ffn_unit(sb, bufGU, bufGU, bufD, bar_fin + 24, bar_fin + 32, bar_fin + 40, cta, warp, lane, tag);
        }
        if (tid == 0) TRACE(5);
        if (cta < 128) {
            const int b = 7 - (cta >> 4), j = cta & 15;
            float* red = reinterpret_cast<float*>(sg + SM_RED);
            gather36<NUNIT, 0>(g_fp + (size_t)b * (DM / 4) + j * 9, red, tid, tag);
            if (tid == 0) TRACE(9);
            bar_cons();
            if (tid < 36) {
                float f = 0.f;
#pragma unroll
                for (int r = 0; r < 14; r++) f += red[r * 36 + tid];
                mbar_wait(bar_ssum, 0);
                const float s = bfr(reinterpret_cast<const float*>(sg + SM_SSUM)[tid]);
                const float gate = bfr(silu_f(bfr(f)));
                const int pos = j * 36 + tid;
                const int col = (pos >> 5) * 32 + ((pos & 3) >> 1) * 16 + (pos & 1) * 8 + ((pos & 31) >> 2);
                out[b * DM + col] = __float2bfloat16_rn(xfin + bfr(s * gate));
            }
        }
        if (tid == 0) TRACE(6);
    } else {
        const int cw = warp - NST - 1, ctid = tid - (NST + 1) * 32;
        uint32_t tag;
        {
            const bool early = cta < NEARLY;
            const int tile = early ? (NCTA - NEARLY) * NST + cta : cta - NEARLY + cw * (NCTA - NEARLY);
            const uint32_t* src = g_q + (tile / TPP) * 256 + lane * 4;
            tag = (ld_relaxed1(&g_state[1]) & 1u) ^ 1u;
            uint4 v0 = ld_relaxed4(src), v1 = ld_relaxed4(src + 128);
            if (ctid == 0) desc[8] = (int)tag;
            __syncwarp();
            __syncthreads();
            if (!early || cw == 3) {
                Spin sp;
                while (true) {
                    const uint32_t bad = (v0.x ^ tag) | (v0.y ^ tag) | (v0.z ^ tag) | (v0.w ^ tag) | (v1.x ^ tag) | (v1.y ^ tag) | (v1.z ^ tag) | (v1.w ^ tag);
                    if (!__any_sync(~0u, bad & 1u)) break;
                    __nanosleep(50);
                    sp.tick();
                    v0 = ld_relaxed4(src); v1 = ld_relaxed4(src + 128);
                }
                uint4* dst = reinterpret_cast<uint4*>(sg + cw * STAGE + 32768) + lane;
                dst[0] = v0; dst[32] = v1;
                __syncwarp();
                if (lane == 0) mbar_arrive(bar_q + cw * 8);
            }
            if (ctid == 96) TRACE(2);
            if (ctid == 0 && cta < 128) {
                uint64_t pol; asm volatile("createpolicy.fractional.L2::evict_first.b64 %0, 1.0;" : "=l"(pol));
                mbar_wait(bar_wfree, 0);
                mbar_expect(bar_wo, STAGE);
                tma3d(sb + SM_WBUF, &maps.wo, 0, 0, cta * 32, bar_wo, pol);
            }
            __syncwarp();
        }
        if (cta < 128) {
            const int g = lane >> 2, t = lane & 3;
            const int hkv = cta >> 3, head = (cta >> 2) & 1, qd = cta & 3;
            const int bfin = 7 - (cta >> 4);
            const int u0 = cw < 2 ? cw * 5 : 10 + (cw - 2) * 4, nu = cw < 2 ? 5 : 4;
#pragma unroll 1
            for (int b = 0; b < NB; b++) {
                const int ph = (b * HKV + hkv) * 2 + head;
                uint2 e;
                {
                    const float2* mlp = g_ml + ph * TPP + cw * 32 + lane;
                    Spin sp;
                    while (true) {
                        e = ld_relaxed2(mlp);
                        const uint32_t miss = __ballot_sync(~0u, ((e.x ^ tag) | (e.y ^ tag)) & 1u);
                        if (!miss) break;
                        __nanosleep(miss == ~0u ? 300 : 20);
                        sp.tick();
                    }
                }
                if (b == TRB && ctid == 96) TRACE(10);
                const uint2* rows = g_po + ((size_t)(ph * 4 + qd) * TPP + cw * 32 + g) * 8 + t * 2;
                uint4 v[4];
#pragma unroll
                for (int i = 0; i < 4; i++) v[i] = ld_relaxed4(rows + i * 64);
                const float m = untagf(e.x);
                float M = m;
#pragma unroll
                for (int o = 16; o; o >>= 1) M = fmaxf(M, __shfl_xor_sync(~0u, M, o));
                const float w = ex2(m - M) * untagf(e.y);
                float L = w;
#pragma unroll
                for (int o = 16; o; o >>= 1) L += __shfl_xor_sync(~0u, L, o);
                float wr[4];
#pragma unroll
                for (int i = 0; i < 4; i++) wr[i] = __shfl_sync(~0u, w, i * 8 + g);
                {
                    Spin sp;
                    while (true) {
                        uint32_t bad = 0;
#pragma unroll
                        for (int i = 0; i < 4; i++) bad |= (v[i].x ^ tag) | (v[i].y ^ tag) | (v[i].z ^ tag) | (v[i].w ^ tag);
                        if (!(bad & 1u)) break;
#pragma unroll
                        for (int i = 0; i < 4; i++) v[i] = ld_relaxed4(rows + i * 64);
                        sp.tick();
                    }
                }
                __syncwarp();
                if (b == TRB && ctid == 96) TRACE(11);
                float acc[8];
#pragma unroll
                for (int k = 0; k < 8; k++) acc[k] = 0.f;
#pragma unroll
                for (int i = 0; i < 4; i++) {
                    const uint32_t u[4] = {v[i].x, v[i].y, v[i].z, v[i].w};
#pragma unroll
                    for (int k = 0; k < 4; k++) {
                        acc[2 * k] = fmaf(wr[i], __uint_as_float((u[k] << 16) & 0xFFFE0000u), acc[2 * k]);
                        acc[2 * k + 1] = fmaf(wr[i], __uint_as_float(u[k] & 0xFFFF0000u), acc[2 * k + 1]);
                    }
                }
#pragma unroll
                for (int k = 0; k < 8; k++) {
                    acc[k] += __shfl_xor_sync(~0u, acc[k], 4);
                    acc[k] += __shfl_xor_sync(~0u, acc[k], 8);
                    acc[k] += __shfl_xor_sync(~0u, acc[k], 16);
                }
                float* part = reinterpret_cast<float*>(sg + SM_PART) + (b & 1) * 160;
                if (g == 0) {
#pragma unroll
                    for (int k = 0; k < 4; k++) *reinterpret_cast<float2*>(part + cw * 40 + k * 8 + 2 * t) = make_float2(acc[k], acc[k + 4]);
                    if (t == 0) *reinterpret_cast<float2*>(part + cw * 40 + 32) = make_float2(M, L);
                }
                bar_comb();
                uint32_t ob[4];
                {
                    float2 ml4[4];
#pragma unroll
                    for (int i = 0; i < 4; i++) ml4[i] = *reinterpret_cast<const float2*>(part + i * 40 + 32);
                    const float MM = fmaxf(fmaxf(ml4[0].x, ml4[1].x), fmaxf(ml4[2].x, ml4[3].x));
                    float sw[4], LL = 0.f;
#pragma unroll
                    for (int i = 0; i < 4; i++) { sw[i] = ex2(ml4[i].x - MM); LL = fmaf(sw[i], ml4[i].y, LL); }
                    const float inv = 1.0f / LL;
#pragma unroll
                    for (int j = 0; j < 4; j++) {
                        float o0 = 0.f, o1 = 0.f;
#pragma unroll
                        for (int i = 0; i < 4; i++) {
                            const float2 pv = *reinterpret_cast<const float2*>(part + i * 40 + j * 8 + 2 * t);
                            o0 = fmaf(sw[i], pv.x, o0); o1 = fmaf(sw[i], pv.y, o1);
                        }
                        ob[j] = pack_bf16(o0 * inv, o1 * inv);
                    }
                }
                if (b == 0) mbar_wait(bar_wo, 0);
                if (b == TRB && ctid == 96) TRACE(12);
                float4* dst = g_sp + ((size_t)cta * NB + b) * (DM / 4) + u0 * 8 + g;
                {
                    float c0[5][4], c1[5][4];
#pragma unroll
                    for (int i = 0; i < 5; i++) {
                        const int u = min(u0 + i, 17);
#pragma unroll
                        for (int k = 0; k < 4; k++) { c0[i][k] = 0.f; c1[i][k] = 0.f; }
#pragma unroll
                        for (int ks = 0; ks < 2; ks++) {
                            uint32_t a[4];
                            ldsm4t(a, addr_w576(sb + SM_WBUF, lane, 2 * u, ks));     mma16816(c0[i], a, ob[2 * ks], ob[2 * ks + 1]);
                            ldsm4t(a, addr_w576(sb + SM_WBUF, lane, 2 * u + 1, ks)); mma16816(c1[i], a, ob[2 * ks], ob[2 * ks + 1]);
                        }
                    }
                    if (t == 0) {
#pragma unroll
                        for (int i = 0; i < 5; i++)
                            if (i < nu) st_relaxed4(dst + i * 8, tagf(c0[i][0], tag), tagf(c0[i][2], tag), tagf(c1[i][0], tag), tagf(c1[i][2], tag));
                        if (b == NB - 2) {
                            const uint32_t inv = tag ^ 1u;
                            for (int i = 0; i < nu; i++) st_relaxed4(dst + DM / 4 + i * 8, inv, inv, inv, inv);
                        }
                    }
                }
                if (b == TRB && ctid == 96) TRACE(13);
                if (b == 7 && ctid == 0) TRACE(7);
                if (b == (bfin < 7 ? bfin + 1 : 7)) {
                    float* red = reinterpret_cast<float*>(sg + SM_RED2);
                    gather36<128, 60>(g_sp + (size_t)bfin * (DM / 4) + (cta & 15) * 9, red, ctid, tag);
                    bar_comb();
                    if (ctid < 36) {
                        float sum = 0.f;
#pragma unroll
                        for (int r = 0; r < 14; r++) sum += red[r * 36 + ctid];
                        reinterpret_cast<float*>(sg + SM_SSUM)[ctid] = sum;
                        mbar_arrive(bar_ssum);
                    }
                    if (ctid == 0) TRACE(8);
                }
            }
        }
    }
}

typedef CUresult (*EncodeFn)(CUtensorMap*, CUtensorMapDataType, cuuint32_t, void*, const cuuint64_t*, const cuuint64_t*,
                             const cuuint32_t*, const cuuint32_t*, CUtensorMapInterleave, CUtensorMapSwizzle,
                             CUtensorMapL2promotion, CUtensorMapFloatOOBfill);

void make_map(EncodeFn enc, CUtensorMap* m, const void* p, int rank, const cuuint64_t* dims, const cuuint64_t* strides,
              const cuuint32_t* box, CUtensorMapSwizzle sw, CUtensorMapL2promotion promo) {
    cuuint32_t es[3] = {1, 1, 1};
    enc(m, CU_TENSOR_MAP_DATA_TYPE_BFLOAT16, rank, const_cast<void*>(p), dims, strides, box, es,
        CU_TENSOR_MAP_INTERLEAVE_NONE, sw, promo, CU_TENSOR_MAP_FLOAT_OOB_FILL_NONE);
}

}

extern "C" void kernel_launch(void* const* d_in, const int* in_sizes, int n_in, void* d_out, int out_size) {
    (void)in_sizes; (void)n_in; (void)out_size;
    static EncodeFn enc = nullptr;
    if (!enc) {
        void* fn = nullptr;
        cudaDriverEntryPointQueryResult qr;
        cudaGetDriverEntryPoint("cuTensorMapEncodeTiled", &fn, cudaEnableDefault, &qr);
        enc = (EncodeFn)fn;
        cudaFuncSetAttribute(fused_decode_kernel, cudaFuncAttributeMaxDynamicSharedMemorySize, SMEM_BYTES);
    }
    Maps maps;
    const cuuint64_t kvrows = (cuuint64_t)NPAIR * SK;
    for (int i = 0; i < 2; i++) {
        cuuint64_t dims[3] = {64, 2, kvrows}, strides[2] = {128, 256};
        cuuint32_t box[3] = {64, 2, TILE};
        make_map(enc, i ? &maps.v : &maps.k, d_in[1 + i], 3, dims, strides, box, CU_TENSOR_MAP_SWIZZLE_128B, CU_TENSOR_MAP_L2_PROMOTION_L2_256B);
    }
    {
        cuuint32_t box[2] = {32, 192};
        cuuint64_t dq[2] = {4096, DM}, sq[1] = {4096 * 2};
        make_map(enc, &maps.wq, d_in[3], 2, dq, sq, box, CU_TENSOR_MAP_SWIZZLE_64B, CU_TENSOR_MAP_L2_PROMOTION_L2_128B);
        cuuint64_t df[2] = {FF, DM}, sf[1] = {FF * 2};
        make_map(enc, &maps.wg, d_in[6], 2, df, sf, box, CU_TENSOR_MAP_SWIZZLE_64B, CU_TENSOR_MAP_L2_PROMOTION_L2_128B);
        make_map(enc, &maps.wu, d_in[7], 2, df, sf, box, CU_TENSOR_MAP_SWIZZLE_64B, CU_TENSOR_MAP_L2_PROMOTION_L2_128B);
    }
    {
        cuuint32_t box[3] = {64, 9, 32};
        cuuint64_t st[2] = {128, DM * 2};
        cuuint64_t d_o[3] = {64, 9, 4096}, d_d[3] = {64, 9, FF};
        make_map(enc, &maps.wo, d_in[4], 3, d_o, st, box, CU_TENSOR_MAP_SWIZZLE_128B, CU_TENSOR_MAP_L2_PROMOTION_L2_256B);
        make_map(enc, &maps.wd, d_in[8], 3, d_d, st, box, CU_TENSOR_MAP_SWIZZLE_128B, CU_TENSOR_MAP_L2_PROMOTION_L2_256B);
    }
    fused_decode_kernel<<<NCTA, NTHREADS, SMEM_BYTES>>>(maps, (const __nv_bfloat16*)d_in[0], (__nv_bfloat16*)d_out);
}
```

```cpp
#include <cuda_runtime.h>
#include <cuda_bf16.h>
#include <cuda.h>
#include <stdint.h>

namespace {

constexpr int NB = 8, DM = 576, HKV = 16, SK = 8192, DH = 128, FF = 4608;
constexpr int NPAIR = NB * HKV;
constexpr int TILE = 64;
constexpr int TPP = SK / TILE;
constexpr int NKV = NPAIR * TPP;
constexpr int NCTA = 132;
constexpr int NST = 4;
constexpr int STAGE = 36864;
constexpr int NUNIT = FF / 32;
constexpr int GRP = 9;
constexpr int NGRP = NUNIT / GRP;
constexpr int NLATE = (NCTA / GRP) * GRP;
constexpr int NEARLY = NUNIT - NLATE;
constexpr int NPLAIN = NCTA - NEARLY;
constexpr int NDYN = NKV - NPLAIN * NST;
constexpr int NDYN1 = NPLAIN * (TPP - NST);
constexpr int XP = 584;
constexpr int NTHREADS = 288;

#define INFLIGHT 3
#define LATECLAIM 400
#define SPIECES 3
#define EPIECES 4
#define HDELAY 700
#define ODELAY 400
#define TAILRULE 0
#define TAILPOLL 900
#define PSLEEP 30
#define LAZY 300
#define TIGHT 20
#define MARGIN 600
#define KV_ORDER 0

constexpr int SM_WBUF = NST * STAGE;
constexpr int SM_XN = SM_WBUF + STAGE;
constexpr int SM_GU = SM_XN + NB * XP * 2;
constexpr int SM_GL = SM_GU + 2 * 8 * 36 * 4;
constexpr int SM_HB = SM_GL + 8 * 36 * 4;
constexpr int SM_RED = SM_HB + 2 * GRP * 32 * 8;
constexpr int SM_PART = SM_RED + 2 * 4 * 36 * 4;
constexpr int SM_BAR = SM_PART + 2 * 4 * 40 * 4;
constexpr int NBAR = 4 * NST + 29;
constexpr int SM_DESC = SM_BAR + NBAR * 8;
constexpr int SM_TOTAL = SM_DESC + 64;
constexpr int SMEM_BYTES = SM_TOTAL + 1024;

struct Maps { CUtensorMap k, v, wq, wg, wu, wo, wd; };

__device__ __align__(128) unsigned g_queue[32];
__device__ __align__(128) unsigned g_state[32];
__device__ __align__(128) uint32_t g_q[NPAIR * 256];
__device__ __align__(128) uint4 g_ml[NKV * 2];
__device__ __align__(128) uint2 g_po[NPAIR * 2 * 4 * TPP * 8];
__device__ __align__(128) uint4 g_ox[128 * NB * 8];
__device__ __align__(128) uint32_t g_sp[HKV * NB * DM];
__device__ __align__(128) uint32_t g_fp[NGRP * NB * DM];
__device__ __align__(128) uint4 g_h[NUNIT * 2 * 32];
#define TRB 7
#define TRACE(i) do {} while (0)

__device__ __forceinline__ uint32_t s2u(const void* p) { return (uint32_t)__cvta_generic_to_shared(p); }
__device__ __forceinline__ void mbar_init(uint32_t b, int c) { asm volatile("mbarrier.init.shared::cta.b64 [%0], %1;" :: "r"(b), "r"(c)); }
__device__ __forceinline__ void mbar_expect(uint32_t b, uint32_t bytes) { asm volatile("mbarrier.arrive.expect_tx.shared::cta.b64 _, [%0], %1;" :: "r"(b), "r"(bytes) : "memory"); }
__device__ __forceinline__ void mbar_arrive(uint32_t b) { asm volatile("mbarrier.arrive.shared::cta.b64 _, [%0];" :: "r"(b) : "memory"); }
__device__ __forceinline__ bool mbar_try(uint32_t b, uint32_t ph) {
    uint32_t ok;
    asm volatile("{\n.reg .pred p;\nmbarrier.try_wait.parity.shared::cta.b64 p, [%1], %2;\nselp.u32 %0, 1, 0, p;\n}" : "=r"(ok) : "r"(b), "r"(ph) : "memory");
    return ok != 0;
}
__device__ __forceinline__ bool mbar_test(uint32_t b, uint32_t ph) {
    uint32_t ok;
    asm volatile("{\n.reg .pred p;\nmbarrier.test_wait.parity.shared::cta.b64 p, [%1], %2;\nselp.u32 %0, 1, 0, p;\n}" : "=r"(ok) : "r"(b), "r"(ph) : "memory");
    return ok != 0;
}
constexpr long long SPIN_LIMIT = 4000000000LL;
__device__ __forceinline__ void mbar_wait(uint32_t b, uint32_t ph) {
    if (mbar_try(b, ph)) return;
    long long t0 = clock64();
    while (!mbar_try(b, ph)) { if (clock64() - t0 > SPIN_LIMIT) __trap(); }
}
struct Spin {
    long long t0 = 0;
    __device__ __forceinline__ void tick() { long long t = clock64(); if (t0 == 0) t0 = t; else if (t - t0 > SPIN_LIMIT) __trap(); }
};
__device__ __forceinline__ void bulk_g2s(uint32_t dst, const void* src, uint32_t bytes, uint32_t bar) {
    asm volatile("cp.async.bulk.shared::cluster.global.mbarrier::complete_tx::bytes [%0], [%1], %2, [%3];" :: "r"(dst), "l"(src), "r"(bytes), "r"(bar) : "memory");
}
__device__ __forceinline__ void tma2d(uint32_t dst, const CUtensorMap* m, int c0, int c1, uint32_t bar) {
    asm volatile("cp.async.bulk.tensor.2d.shared::cluster.global.mbarrier::complete_tx::bytes [%0], [%1, {%3, %4}], [%2];" :: "r"(dst), "l"(m), "r"(bar), "r"(c0), "r"(c1) : "memory");
}
__device__ __forceinline__ void tma3d(uint32_t dst, const CUtensorMap* m, int c0, int c1, int c2, uint32_t bar, uint64_t pol) {
    asm volatile("cp.async.bulk.tensor.3d.shared::cluster.global.mbarrier::complete_tx::bytes.L2::cache_hint [%0], [%1, {%3, %4, %5}], [%2], %6;" :: "r"(dst), "l"(m), "r"(bar), "r"(c0), "r"(c1), "r"(c2), "l"(pol) : "memory");
}
__device__ __forceinline__ void ldsm4(uint32_t (&r)[4], uint32_t a) {
    asm volatile("ldmatrix.sync.aligned.m8n8.x4.shared.b16 {%0,%1,%2,%3}, [%4];" : "=r"(r[0]), "=r"(r[1]), "=r"(r[2]), "=r"(r[3]) : "r"(a));
}
__device__ __forceinline__ void ldsm4t(uint32_t (&r)[4], uint32_t a) {
    asm volatile("ldmatrix.sync.aligned.m8n8.x4.trans.shared.b16 {%0,%1,%2,%3}, [%4];" : "=r"(r[0]), "=r"(r[1]), "=r"(r[2]), "=r"(r[3]) : "r"(a));
}
__device__ __forceinline__ void mma16816(float (&c)[4], const uint32_t (&a)[4], uint32_t b0, uint32_t b1) {
    asm("mma.sync.aligned.m16n8k16.row.col.f32.bf16.bf16.f32 {%0,%1,%2,%3}, {%4,%5,%6,%7}, {%8,%9}, {%0,%1,%2,%3};"
                 : "+f"(c[0]), "+f"(c[1]), "+f"(c[2]), "+f"(c[3]) : "r"(a[0]), "r"(a[1]), "r"(a[2]), "r"(a[3]), "r"(b0), "r"(b1));
}
__device__ __forceinline__ uint4 ld_relaxed4(const void* p) {
    uint4 v; asm volatile("ld.relaxed.gpu.global.v4.u32 {%0,%1,%2,%3}, [%4];" : "=r"(v.x), "=r"(v.y), "=r"(v.z), "=r"(v.w) : "l"(p) : "memory"); return v;
}
__device__ __forceinline__ uint2 ld_relaxed2(const void* p) {
    uint2 v; asm volatile("ld.relaxed.gpu.global.v2.u32 {%0,%1}, [%2];" : "=r"(v.x), "=r"(v.y) : "l"(p) : "memory"); return v;
}
__device__ __forceinline__ uint32_t ld_relaxed1(const void* p) {
    uint32_t v; asm volatile("ld.relaxed.gpu.global.u32 %0, [%1];" : "=r"(v) : "l"(p) : "memory"); return v;
}
__device__ __forceinline__ uint32_t ld_acquire1(const void* p) {
    uint32_t v; asm volatile("ld.acquire.gpu.global.u32 %0, [%1];" : "=r"(v) : "l"(p) : "memory"); return v;
}
__device__ __forceinline__ void st_relaxed4(void* p, uint32_t a, uint32_t b, uint32_t c, uint32_t d) {
    asm volatile("st.relaxed.gpu.global.v4.u32 [%0], {%1,%2,%3,%4};" :: "l"(p), "r"(a), "r"(b), "r"(c), "r"(d) : "memory");
}
__device__ __forceinline__ void st_relaxed1(void* p, uint32_t a) {
    asm volatile("st.relaxed.gpu.global.u32 [%0], %1;" :: "l"(p), "r"(a) : "memory");
}
__device__ __forceinline__ void st_relaxed2(void* p, uint32_t a, uint32_t b) {
    asm volatile("st.relaxed.gpu.global.v2.u32 [%0], {%1,%2};" :: "l"(p), "r"(a), "r"(b) : "memory");
}
__device__ __forceinline__ uint32_t lds32(uint32_t a) { uint32_t v; asm volatile("ld.shared.u32 %0, [%1];" : "=r"(v) : "r"(a) : "memory"); return v; }
__device__ __forceinline__ uint4 lds128(uint32_t a) { uint4 v; asm volatile("ld.shared.v4.u32 {%0,%1,%2,%3}, [%4];" : "=r"(v.x), "=r"(v.y), "=r"(v.z), "=r"(v.w) : "r"(a) : "memory"); return v; }
__device__ __forceinline__ void bar_cons() { asm volatile("bar.sync 1, 128;" ::: "memory"); }
__device__ __forceinline__ void bar_comb() { asm volatile("bar.sync 2, 128;" ::: "memory"); }
__device__ __forceinline__ float bfr(float v) { return __bfloat162float(__float2bfloat16_rn(v)); }
__device__ __forceinline__ uint32_t pack_bf16(float lo, float hi) {
    uint32_t r; asm("cvt.rn.bf16x2.f32 %0, %1, %2;" : "=r"(r) : "f"(hi), "f"(lo)); return r;
}
__device__ __forceinline__ float ex2(float x) { float y; asm("ex2.approx.ftz.f32 %0, %1;" : "=f"(y) : "f"(x)); return y; }
__device__ __forceinline__ float silu_f(float v) { return __fdividef(v, 1.0f + __expf(-v)); }
__device__ __forceinline__ uint32_t tagf(float v, uint32_t tag) { return (__float_as_uint(v) & ~1u) | tag; }
__device__ __forceinline__ float untagf(uint32_t w) { return __uint_as_float(w & ~1u); }
__device__ __forceinline__ uint32_t bad4(const uint4& v, uint32_t tag) { return ((v.x ^ tag) | (v.y ^ tag) | (v.z ^ tag) | (v.w ^ tag)) & 1u; }
__device__ __forceinline__ uint32_t pack_tag(float lo, float hi, uint32_t tag) {
    uint32_t l = ((__float_as_uint(lo) + 0x10000u) >> 16) & 0xFFFEu;
    uint32_t h = pack_bf16(0.f, hi) & 0xFFFF0000u;
    return h | l | tag;
}

__device__ __forceinline__ int dyn_tile(int n) {
    if (n >= NDYN1) return NPLAIN * TPP + (n - NDYN1);
    const int p = n / (TPP - NST);
    return p * TPP + NST + (n - p * (TPP - NST));
}

__device__ __forceinline__ uint32_t addr_w32(uint32_t base, int lane, int mt, int ks) {
    int mat = lane >> 3, row = ks * 16 + (mat >> 1) * 8 + (lane & 7), c = mt * 2 + (mat & 1);
    return base + row * 64 + ((c ^ ((row >> 1) & 3)) << 4);
}
__device__ __forceinline__ uint32_t addr_kv(uint32_t base, int key, int chunk) {
    return base + (chunk >> 3) * 8192 + key * 128 + (((chunk & 7) ^ (key & 7)) << 4);
}

template <int NKS>
__device__ __forceinline__ void proj32(float (&acc)[4], uint32_t wbase, uint32_t bar, uint32_t xn, int lane, int mt, int ks0) {
    uint32_t xb[NKS / 2][4];
    const uint32_t xa = xn + ((lane & 7) * XP + (lane >> 3) * 8 + ks0 * 16) * 2;
#pragma unroll
    for (int i = 0; i < NKS / 2; i++) ldsm4(xb[i], xa + i * 64);
    float a4[4][4];
#pragma unroll
    for (int i = 0; i < 4; i++) { a4[i][0] = a4[i][1] = a4[i][2] = a4[i][3] = 0.f; }
    const uint32_t wa = addr_w32(wbase, lane, mt, ks0);
    if (ks0 < 12) mbar_wait(bar, 0);
    mbar_wait(bar + 8, 0);
    if (ks0 + NKS > 24) mbar_wait(bar + 16, 0);
#pragma unroll
    for (int i = 0; i < NKS; i++) {
        uint32_t a[4];
        ldsm4t(a, wa + i * 1024);
        mma16816(a4[i & 3], a, xb[i >> 1][(i & 1) * 2], xb[i >> 1][(i & 1) * 2 + 1]);
    }
#pragma unroll
    for (int i = 0; i < 4; i++) acc[i] = (a4[0][i] + a4[1][i]) + (a4[2][i] + a4[3][i]);
}

__device__ __forceinline__ void put_frag(float* dst, const float (&acc)[4], int mt, int g, int t) {
    dst[(2 * t) * 36 + mt * 16 + g] = acc[0];
    dst[(2 * t + 1) * 36 + mt * 16 + g] = acc[1];
    dst[(2 * t) * 36 + mt * 16 + g + 8] = acc[2];
    dst[(2 * t + 1) * 36 + mt * 16 + g + 8] = acc[3];
}
__device__ __forceinline__ void put_tile(uint32_t* dst, uint32_t w0, uint32_t w1, uint32_t w2, uint32_t w3, bool upper) {
    st_relaxed1(dst, w0); st_relaxed1(dst + DM, w1);
    if (upper) { st_relaxed1(dst + 8, w2); st_relaxed1(dst + DM + 8, w3); }
}
__device__ __forceinline__ uint32_t* fp_slot(int unit, int warp, int g, int t) {
    return g_fp + ((unit / GRP) * NB + 2 * t) * DM + (unit % GRP) * 64 + warp * 16 + g;
}

template <bool LATE>
__device__ __forceinline__ void ffn_unit(uint32_t sb, uint32_t bufG, uint32_t bufU, uint32_t bufD, uint32_t barG, uint32_t barU,
                                         uint32_t barD, int unit, int warp, int lane, uint32_t tag) {
    const int g = lane >> 2, t = lane & 3;
    const int hf = warp >> 1, mt = warp & 1;
    float* gu = reinterpret_cast<float*>(__cvta_shared_to_generic(sb + SM_GU));
    float acc[4];
    if (LATE) { mbar_wait(barG, 0); proj32<18>(acc, bufU, barU, sb + SM_XN, lane, mt, hf * 18); }
    else proj32<36>(acc, hf ? bufU : bufG, hf ? barU : barG, sb + SM_XN, lane, mt, 0);
    if (lane == 0 && warp == 2) TRACE(33);
    put_frag(gu + hf * 288, acc, mt, g, t);
    bar_cons();
    if (warp < 2) {
        uint32_t hw[2];
#pragma unroll
        for (int j = 0; j < 2; j++) {
            const int f = g * 36 + warp * 16 + j * 8 + 2 * t;
            const float2 p0 = *reinterpret_cast<const float2*>(gu + f), p1 = *reinterpret_cast<const float2*>(gu + 288 + f);
            float2 gg = p0, uu = p1;
            if (LATE) { gg = *reinterpret_cast<const float2*>(gu + 576 + f); uu = make_float2(p0.x + p1.x, p0.y + p1.y); }
            hw[j] = pack_bf16(bfr(silu_f(bfr(gg.x))) * bfr(uu.x), bfr(silu_f(bfr(gg.y))) * bfr(uu.y));
        }
        st_relaxed4(g_h + (unit * 2 + warp) * 32 + lane, (hw[0] << 16) | tag, (hw[0] & 0xFFFF0000u) | tag, (hw[1] << 16) | tag, (hw[1] & 0xFFFF0000u) | tag);
    }
    if (lane == 0 && warp == 0) TRACE(34);
    {
        const uint4* src = g_h + (unit / GRP) * (2 * GRP * 32) + warp * 32 + lane;
        uint4 v[5];
        uint32_t pend = warp < 2 ? 0x1Fu : 0xFu;
        Spin sp;
        if (LATE && HDELAY) __nanosleep(HDELAY);
        while (true) {
#pragma unroll
            for (int i = 0; i < 5; i++)
                if (pend >> i & 1) v[i] = ld_relaxed4(src + i * 128);
#pragma unroll
            for (int i = 0; i < 5; i++)
                if ((pend >> i & 1) && !__any_sync(~0u, bad4(v[i], tag))) {
                    pend &= ~(1u << i);
                    asm volatile("st.shared.v2.u32 [%0], {%1, %2};" :: "r"(sb + SM_HB + ((i * 4 + warp) * 32 + lane) * 8),
                                 "r"(__byte_perm(v[i].x, v[i].y, 0x7632)), "r"(__byte_perm(v[i].z, v[i].w, 0x7632)) : "memory");
                }
            if (!pend) break;
            __nanosleep(PSLEEP);
            sp.tick();
        }
    }
    bar_cons();
    uint2 hb[2 * GRP];
#pragma unroll
    for (int ks = 0; ks < 2 * GRP; ks++)
        asm volatile("ld.shared.v2.u32 {%0, %1}, [%2];" : "=r"(hb[ks].x), "=r"(hb[ks].y) : "r"(sb + SM_HB + (ks * 32 + lane) * 8) : "memory");
    if (lane == 0 && warp == 0) TRACE(35);
    mbar_wait(barD, 0); mbar_wait(barD + 8, 0); mbar_wait(barD + 16, 0);
    if (lane == 0 && warp == 0) TRACE(36);

    float c0[4] = {0.f, 0.f, 0.f, 0.f}, c1[4] = {0.f, 0.f, 0.f, 0.f}, c2[4] = {0.f, 0.f, 0.f, 0.f};
    {
        const int m4 = lane >> 3, row = (m4 >> 1) * 8 + (lane & 7), c = warp * 2 + (m4 & 1);
        const uint32_t a0 = bufD + row * 128 + ((c ^ (lane & 7)) << 4);
#pragma unroll
        for (int ks = 0; ks < 2 * GRP; ks++) {
            uint32_t a[4];
            ldsm4t(a, a0 + ks * 2048);
            if (ks % 3 == 0) mma16816(c0, a, hb[ks].x, hb[ks].y);
            else if (ks % 3 == 1) mma16816(c1, a, hb[ks].x, hb[ks].y);
            else mma16816(c2, a, hb[ks].x, hb[ks].y);
        }
    }
    put_tile(fp_slot(unit, warp, g, t), tagf(c0[0] + c1[0] + c2[0], tag), tagf(c0[1] + c1[1] + c2[1], tag),
             tagf(c0[2] + c1[2] + c2[2], tag), tagf(c0[3] + c1[3] + c2[3], tag), true);
}

__device__ __forceinline__ void gather16(const uint32_t* base, float* red, int tid, uint32_t tag) {
    const int f = tid & 7;
    const uint32_t* src = base + (tid >> 3) * (NB * DM) + f * 4;
    uint4 v0, v1 = make_uint4(tag, tag, tag, tag);
    Spin sp;
    while (true) {
        v0 = ld_relaxed4(src);
        if (f == 0) v1 = ld_relaxed4(src + 32);
        if (!__any_sync(~0u, bad4(v0, tag) | bad4(v1, tag))) break;
        __nanosleep(PSLEEP);
        sp.tick();
    }
    float a[8] = {untagf(v0.x), untagf(v0.y), untagf(v0.z), untagf(v0.w), untagf(v1.x), untagf(v1.y), untagf(v1.z), untagf(v1.w)};
#pragma unroll
    for (int i = 0; i < 8; i++) { a[i] += __shfl_xor_sync(~0u, a[i], 8); a[i] += __shfl_xor_sync(~0u, a[i], 16); }
    if ((tid & 31) < 8) {
        float* r = red + (tid >> 5) * 36;
        *reinterpret_cast<float4*>(r + f * 4) = make_float4(a[0], a[1], a[2], a[3]);
        if (f == 0) *reinterpret_cast<float4*>(r + 32) = make_float4(a[4], a[5], a[6], a[7]);
    }
}

__global__ void __launch_bounds__(NTHREADS, 1)
fused_decode_kernel(const __grid_constant__ Maps maps, const __nv_bfloat16* __restrict__ x, __nv_bfloat16* __restrict__ out) {
    extern __shared__ uint8_t smem_raw[];
    const uint32_t sb = (s2u(smem_raw) + 1023u) & ~1023u;
    uint8_t* sg = smem_raw + (sb - s2u(smem_raw));
    const int tid = threadIdx.x, warp = tid >> 5, lane = tid & 31, cta = blockIdx.x;
    const uint32_t bar_full = sb + SM_BAR, bar_empty = bar_full + NST * 8;
    const uint32_t bar_q = bar_empty + NST * 8, bar_v = bar_q + NST * 8;
    const uint32_t bar_wq = bar_v + NST * 8, bar_wg = bar_wq + 24;
    const uint32_t bar_e = bar_wg + 24;
    const uint32_t bar_lu = bar_e + 72, bar_ld = bar_lu + 24, bar_wo = bar_ld + 24;
    const uint32_t bar_ssum = bar_wo + 32, bar_first = bar_ssum + 8, bar_wfree = bar_first + 8, bar_gdone = bar_wfree + 8;
    volatile int* desc = reinterpret_cast<volatile int*>(sg + SM_DESC);

    if (tid < 7) asm volatile("prefetch.tensormap [%0];" :: "l"(reinterpret_cast<const CUtensorMap*>(&maps) + tid) : "memory");

    if (warp == NST) {
        uint64_t pol; asm volatile("createpolicy.fractional.L2::evict_first.b64 %0, 1.0;" : "=l"(pol));
        constexpr int FN = 5, F0 = FN - INFLIGHT;
        uint32_t fifo[FN];
#pragma unroll
        for (int i = 0; i < FN; i++) fifo[i] = 0;
        auto gate = [&](int n) { for (int i = F0; i < F0 + n; i++) if (fifo[i]) mbar_wait(fifo[i] & ~1u, fifo[i] & 1u); };
        auto push = [&](uint32_t bar, uint32_t par) {
#pragma unroll
            for (int i = 0; i + 1 < FN; i++) fifo[i] = fifo[i + 1];
            fifo[FN - 1] = bar | par;
        };
        auto issue_half = [&](const CUtensorMap* m, int tile, uint32_t dst, uint32_t bar, uint32_t par) {
            mbar_expect(bar, 16384);
            tma3d(dst, m, 0, tile * TILE, 0, bar, pol);
            push(bar, par);
        };
        auto issue_k = [&](int tile, int st, uint32_t par) { desc[st] = tile; issue_half(&maps.k, tile, sb + st * STAGE, bar_full + st * 8, par); };
        auto issue_v = [&](int tile, int st, uint32_t par) { issue_half(&maps.v, tile, sb + st * STAGE + 16384, bar_v + st * 8, par); };
        auto piece = [&](const CUtensorMap* m, int c0, int c1, uint32_t dst, uint32_t bar, uint32_t bytes) {
            mbar_expect(bar, bytes);
            tma2d(dst, m, c0, c1, bar);
            push(bar, 0);
        };
        auto col_piece = [&](const CUtensorMap* m, int unit, int i, uint32_t buf, uint32_t bar) { piece(m, unit * 32, i * 192, buf + i * 12288, bar + i * 8, 12288); };
        auto down_piece = [&](int unit, int i, uint32_t buf, uint32_t bar) {
            piece(&maps.wd, (unit % GRP) * 64, (unit / GRP) * (GRP * 32) + i * 96, buf + i * 12288, bar + i * 8, 12288);
        };
        auto gate4 = [&]() { const uint32_t f = fifo[FN - SPIECES]; if (f) mbar_wait(f & ~1u, f & 1u); };
        const bool early = cta >= NPLAIN;
        const int eunit = NLATE + cta - NPLAIN;
        int next = 0;
        auto claim = [&]() { return (int)atomicAdd(&g_queue[0], 1u); };
        if (lane == 0) desc[9] = 0;
        if (lane == 0) {
            TRACE(0);
            for (int i = 0; i < NST; i++) { mbar_init(bar_full + i * 8, 1); mbar_init(bar_v + i * 8, 1); mbar_init(bar_empty + i * 8, 1); mbar_init(bar_q + i * 8, 1); }
            for (int i = 0; i < 25; i++) mbar_init(bar_wq + i * 8, 1);
            mbar_init(bar_ssum, 4); mbar_init(bar_first, 1); mbar_init(bar_wfree, 1); mbar_init(bar_gdone, 2);
            asm volatile("fence.mbarrier_init.release.cluster;" ::: "memory");
            if (cta < 128) for (int i = 0; i < 3; i++) col_piece(&maps.wq, cta, i, sb + SM_WBUF, bar_wq);
            if (early) col_piece(&maps.wg, eunit, 0, sb, bar_e);
            else issue_k(cta * TPP, 0, 0);
            next = claim();
        }
        __syncwarp();
        asm volatile("bar.arrive 0, %0;" :: "n"(NTHREADS) : "memory");
        if (lane == 0) {
            if (early) {
                for (int i = 1; i < 3; i++) { gate4(); col_piece(&maps.wg, eunit, i, sb, bar_e); }
                for (int i = 0; i < 3; i++) { gate4(); col_piece(&maps.wu, eunit, i, sb + STAGE, bar_e + 24); }
                for (int i = 0; i < 3; i++) { gate4(); down_piece(eunit, i, sb + 2 * STAGE, bar_e + 48); }
                const int tile = dyn_tile(next);
                gate4(); issue_k(tile, 3, 0); mbar_arrive(bar_first);
                next = claim();
                gate4(); issue_v(tile, 3, 0);
            } else {
                gate4(); issue_v(cta * TPP, 0, 0);
#pragma unroll
                for (int i = 1; i < NST; i++) { gate4(); issue_k(cta * TPP + i, i, 0); gate4(); issue_v(cta * TPP + i, i, 0); }
            }
            if (cta < 128) mbar_wait(bar_wfree, 0);
            if (cta < NLATE) for (int i = 0; i < 3; i++) { gate4(); col_piece(&maps.wg, cta, i, sb + SM_WBUF, bar_wg); }
            if (early) mbar_wait(bar_q + 24, 0);
            int st = 0; uint32_t ph = 0;
            while (true) {
                if (next < 0) {
                    Spin sp;
                    while (!mbar_test(fifo[F0] & ~1u, fifo[F0] & 1u)) {
                        if (ld_relaxed1(&g_queue[0]) >= (unsigned)NDYN) { next = NDYN; break; }
                        sp.tick();
                    }
                    if (next >= NDYN) break;
                    mbar_wait(bar_empty + st * 8, ph);
                    next = claim();
                } else {
                    gate(1);
                    mbar_wait(bar_empty + st * 8, ph);
                }
                if (next >= NDYN) break;
                const int tile = dyn_tile(next);
                const uint32_t par = (early && st < 3) ? ph : ph ^ 1u;
                issue_k(tile, st, par);
                desc[9] = next;
                mbar_expect(bar_q + st * 8, 1024);
                bulk_g2s(sb + st * STAGE + 32768, g_q + (tile / TPP) * 256, 1024, bar_q + st * 8);
                next = next >= NDYN - LATECLAIM ? -1 : claim();
                if (next >= 0) gate(1);
                issue_v(tile, st, par);
                if (++st == NST) { st = 0; ph ^= 1; }
            }
            desc[9] = NDYN;
            TRACE(3);
            const int stU = st;
            desc[4] = stU;
#pragma unroll
            for (int i = 0; i < F0; i++) fifo[i] = 0;
            int ends = 0, k = cta < NLATE ? 0 : 6;
            const int kend = cta < 128 ? 10 : 6;
            if (cta < NLATE) mbar_wait(bar_gdone, 0);
            Spin sp;
            while (ends < NST || k < kend) {
                if (ends < NST && mbar_test(bar_empty + st * 8, ph)) {
#pragma unroll
                    for (int i = 0; i < FN; i++) if ((fifo[i] & ~1u) == bar_full + st * 8) fifo[i] = 0;
                    desc[st] = -1;
                    mbar_arrive(bar_full + st * 8);
                    if (++st == NST) { st = 0; ph ^= 1; }
                    ends++;
                }
                if (k < kend && ends >= (k < 3 ? 1 : k < 6 ? 2 : 0) && (fifo[FN - EPIECES] == 0 || mbar_test(fifo[FN - EPIECES] & ~1u, fifo[FN - EPIECES] & 1u))) {
                    if (k < 3) col_piece(&maps.wu, cta, k, sb + stU * STAGE, bar_lu);
                    else if (k < 6) down_piece(cta, k - 3, sb + ((stU + 1) % NST) * STAGE, bar_ld);
                    else piece(&maps.wo, (cta & 7) * 72, (cta >> 3) * 256 + (k - 6) * 64, sb + SM_WBUF + (k - 6) * 9216, bar_wo + (k - 6) * 8, 9216);
                    k++;
                }
                sp.tick();
            }
            if (atomicAdd(&g_state[0], 1u) == NCTA - 1) {
                g_queue[0] = 0; g_state[0] = 0;
                g_state[1] = g_state[1] + 1;
            }
        }
    } else if (warp < NST) {
        const int g = lane >> 2, t = lane & 3;
        float xfin = 0.f;
        if (tid < 36 && cta < 128) xfin = __bfloat162float(x[cta * 36 + tid]);
        {
            uint32_t xr[2][9];
#pragma unroll
            for (int r = 0; r < 2; r++)
#pragma unroll
                for (int i = 0; i < 9; i++)
                    xr[r][i] = __ldg(reinterpret_cast<const uint32_t*>(x + (warp * 2 + r) * DM) + i * 32 + lane);
#pragma unroll
            for (int r = 0; r < 2; r++) {
                float v[18], s = 0.f;
#pragma unroll
                for (int i = 0; i < 9; i++) { v[2 * i] = __uint_as_float(xr[r][i] << 16); v[2 * i + 1] = __uint_as_float(xr[r][i] & 0xFFFF0000u); s += v[2 * i] + v[2 * i + 1]; }
#pragma unroll
                for (int o = 16; o; o >>= 1) s += __shfl_xor_sync(~0u, s, o);
                const float mean = s * (1.0f / DM);
                float q = 0.f;
#pragma unroll
                for (int i = 0; i < 18; i++) { float d = v[i] - mean; q += d * d; }
#pragma unroll
                for (int o = 16; o; o >>= 1) q += __shfl_xor_sync(~0u, q, o);
                const float mb = bfr(mean), rden = __frcp_rn(bfr(__fsqrt_rn(bfr(bfr(q * (1.0f / DM)) + 1e-5f))));
                uint32_t* xn = reinterpret_cast<uint32_t*>(sg + SM_XN) + (warp * 2 + r) * (XP / 2);
#pragma unroll
                for (int i = 0; i < 9; i++) xn[i * 32 + lane] = pack_bf16(bfr(v[2 * i] - mb) * rden, bfr(v[2 * i + 1] - mb) * rden);
            }
        }
        if (tid == 0) TRACE(14);
        asm volatile("bar.sync 0, %0;" :: "n"(NTHREADS) : "memory");
        const uint32_t tag = (uint32_t)desc[8];
        if (cta < 128) {
            float acc[4];
            const int mt = warp & 1, kh = warp >> 1;
            proj32<18>(acc, sb + SM_WBUF, bar_wq, sb + SM_XN, lane, mt, kh * 18);
            if (tid == 0) TRACE(15);
            float* gu = reinterpret_cast<float*>(sg + SM_GU);
            put_frag(gu + kh * 288, acc, mt, g, t);
            bar_cons();
            {
                const int b = tid >> 4, c = (tid & 15) * 2;
                const float q0 = gu[b * 36 + c] + gu[(8 + b) * 36 + c], q1 = gu[b * 36 + c + 1] + gu[(8 + b) * 36 + c + 1];
                const int hq = cta >> 2, d = (cta & 3) * 32 + c;
                const int off = (b * HKV + (hq >> 1)) * 256 + (hq & 1) * 128 + (d >> 4) * 16 + ((d & 7) >> 1) * 4 + ((d >> 3) & 1) * 2;
                const uint32_t pk = pack_bf16(q0, q1);
                st_relaxed2(g_q + off, (pk << 16) | tag, (pk & 0xFFFF0000u) | tag);
            }
            if (tid == 0) TRACE(1);
            bar_cons();
            if (tid == 0) mbar_arrive(bar_wfree);
        }
        if (cta >= NPLAIN) {
            ffn_unit<false>(sb, sb, sb + STAGE, sb + 2 * STAGE, bar_e, bar_e + 24, bar_e + 48, NLATE + cta - NPLAIN, warp, lane, tag);
            bar_cons();
            if (warp < 3 && lane == 0) mbar_arrive(bar_empty + warp * 8);
        }
        const uint32_t kb = sb + warp * STAGE, vb = kb + 16384, qb = kb + 32768;
        const int mat = lane >> 3, r8 = lane & 7;
        const int kkey = (mat & 1) ? 8 + ((r8 + 4) & 7) : r8;
        const int rho = (r8 >> 1) + (mat >> 1) * 4;
        const int vkey = (r8 & 1) ? 8 + ((rho + 4) & 7) : rho;
        const float sc = 0.08838834764831845f * 1.4426950408889634f;
        uint32_t ph = 0;
        while (true) {
            mbar_wait(bar_full + warp * 8, ph);
            ph ^= 1;
            const int tile = desc[warp];
            if (tile < 0) break;
            mbar_wait(bar_q + warp * 8, ph ^ 1u);
            uint32_t qf[16];
            {
                const bool on = (g == 0) || (g == 2);
                uint4 v[8];
                uint32_t bad = 0;
#pragma unroll
                for (int j = 0; j < 8; j++) {
                    v[j] = make_uint4(tag, tag, tag, tag);
                    if (on) v[j] = lds128(qb + (g >> 1) * 512 + j * 64 + t * 16);
                    bad |= (v[j].x ^ tag) | (v[j].y ^ tag) | (v[j].z ^ tag) | (v[j].w ^ tag);
                }
                if (__any_sync(~0u, bad & 1u)) {
                    Spin sp;
                    do {
                        bad = 0;
                        if (on) {
#pragma unroll
                            for (int j = 0; j < 8; j++) v[j] = ld_relaxed4(g_q + (tile / TPP) * 256 + (g >> 1) * 128 + j * 16 + t * 4);
#pragma unroll
                            for (int j = 0; j < 8; j++) bad |= bad4(v[j], tag);
                        }
                        sp.tick();
                    } while (__any_sync(~0u, bad));
                }
#pragma unroll
                for (int j = 0; j < 8; j++) { qf[2 * j] = __byte_perm(v[j].x, v[j].y, 0x7632); qf[2 * j + 1] = __byte_perm(v[j].z, v[j].w, 0x7632); }
            }
            float s[4][4];
#pragma unroll
            for (int mt = 0; mt < 4; mt++) { s[mt][0] = s[mt][1] = s[mt][2] = s[mt][3] = 0.f; }
#pragma unroll
            for (int ks = 0; ks < 8; ks++)
#pragma unroll
                for (int mt = 0; mt < 4; mt++) {
                    uint32_t a[4];
                    ldsm4(a, addr_kv(kb, mt * 16 + kkey, 2 * ks + (mat >> 1)));
                    mma16816(s[mt], a, qf[2 * ks], qf[2 * ks + 1]);
                }
            float m = fmaxf(fmaxf(fmaxf(s[0][0], s[0][2]), fmaxf(s[1][0], s[1][2])), fmaxf(fmaxf(s[2][0], s[2][2]), fmaxf(s[3][0], s[3][2])));
            m = fmaxf(m, __shfl_xor_sync(~0u, m, 4));
            m = fmaxf(m, __shfl_xor_sync(~0u, m, 8));
            m = fmaxf(m, __shfl_xor_sync(~0u, m, 16));
            const float ms = untagf(__float_as_uint(m * sc));
            float l = 0.f;
            uint32_t pb[4][2];
#pragma unroll
            for (int mt = 0; mt < 4; mt++) {
                const float p0 = ex2(fmaf(s[mt][0], sc, -ms)), p1 = ex2(fmaf(s[mt][2], sc, -ms));
                l += p0 + p1;
                const uint32_t pk = pack_bf16(p0, p1);
                pb[mt][0] = __shfl_sync(~0u, pk, 4 * t + (g & 1));
                pb[mt][1] = __shfl_sync(~0u, pk, 4 * (t + 4) + (g & 1));
            }
            l += __shfl_xor_sync(~0u, l, 4);
            l += __shfl_xor_sync(~0u, l, 8);
            l += __shfl_xor_sync(~0u, l, 16);
            float o[8][4];
#pragma unroll
            for (int i = 0; i < 8; i++) { o[i][0] = o[i][1] = o[i][2] = o[i][3] = 0.f; }
            mbar_wait(bar_v + warp * 8, ph ^ 1u);
#pragma unroll
            for (int kk = 0; kk < 4; kk++)
#pragma unroll
                for (int i = 0; i < 8; i++) {
                    uint32_t a[4];
                    ldsm4t(a, addr_kv(vb, kk * 16 + vkey, 2 * i + (mat & 1)));
                    mma16816(o[i], a, pb[kk][0], pb[kk][1]);
                }
            __syncwarp();
            if (lane == 0) mbar_arrive(bar_empty + warp * 8);
            const float inv = 1.0f / l;
            const float inv1 = __shfl_down_sync(~0u, inv, 1);
            const int pair = tile / TPP, tt = tile % TPP;
            if (t == 0) {
                uint2* dst = g_po + ((size_t)pair * 8 * TPP + tt) * 8 + g;
#pragma unroll
                for (int qd = 0; qd < 4; qd++) {
                    st_relaxed2(dst + (size_t)qd * TPP * 8,
                                pack_tag(o[2 * qd][0] * inv, o[2 * qd][2] * inv, tag), pack_tag(o[2 * qd + 1][0] * inv, o[2 * qd + 1][2] * inv, tag));
                    st_relaxed2(dst + (size_t)(4 + qd) * TPP * 8,
                                pack_tag(o[2 * qd][1] * inv1, o[2 * qd][3] * inv1, tag), pack_tag(o[2 * qd + 1][1] * inv1, o[2 * qd + 1][3] * inv1, tag));
                }
            }
            {
                const uint32_t m_ = tagf(ms, tag), l_ = tagf(l, tag);
                const uint32_t m0 = __shfl_sync(~0u, m_, 0), l0 = __shfl_sync(~0u, l_, 0), m1 = __shfl_sync(~0u, m_, 1), l1 = __shfl_sync(~0u, l_, 1);
                if (lane < 2) st_relaxed4(g_ml + tile * 2 + lane, m0, l0, m1, l1);
            }
        }
        if (tid == 0) TRACE(4);
        if (cta < NLATE) {
            {
                const uint32_t inv = tag ^ 1u;
                put_tile(fp_slot(cta, warp, g, t), inv, inv, inv, inv, true);
                if (warp < 2) st_relaxed4(g_h + (cta * 2 + warp) * 32 + lane, inv, inv, inv, inv);
            }
            const int stU = desc[4];
            ffn_unit<true>(sb, 0, sb + stU * STAGE, sb + ((stU + 1) % NST) * STAGE, bar_gdone, bar_lu, bar_ld, cta, warp, lane, tag);
        }
        if (tid == 0) TRACE(5);
        if (cta < 128) {
            float* red = reinterpret_cast<float*>(sg + SM_RED);
            gather16(g_fp + cta * 36, red, tid, tag);
            if (tid == 0) TRACE(9);
            bar_cons();
            if (tid < 36) {
                const float f = (red[tid] + red[36 + tid]) + (red[72 + tid] + red[108 + tid]);
                const float gate = bfr(silu_f(bfr(f)));
                mbar_wait(bar_ssum, 0);
                const float s = bfr((red[144 + tid] + red[180 + tid]) + (red[216 + tid] + red[252 + tid]));
                out[cta * 36 + tid] = __float2bfloat16_rn(xfin + bfr(s * gate));
            }
        }
        if (tid == 0) TRACE(6);
    } else {
        const int cw = warp - NST - 1, ctid = tid - (NST + 1) * 32;
        uint32_t tag;
        {
            const bool early = cta >= NPLAIN;
            const uint32_t* src = g_q + cta * 256 + lane * 4;
            tag = (ld_relaxed1(&g_state[1]) & 1u) ^ 1u;
            uint4 v0 = make_uint4(0, 0, 0, 0), v1 = v0;
            if (cw == 3 && !early) { v0 = ld_relaxed4(src); v1 = ld_relaxed4(src + 128); }
            if (ctid == 0) desc[8] = (int)tag;
            __syncwarp();
            asm volatile("bar.sync 0, %0;" :: "n"(NTHREADS) : "memory");
            if (cw == 3) {
                if (early) {
                    mbar_wait(bar_first, 0);
                    src = g_q + (desc[3] / TPP) * 256 + lane * 4;
                    v0 = ld_relaxed4(src); v1 = ld_relaxed4(src + 128);
                }
                Spin sp;
                while (true) {
                    const uint32_t bad = (v0.x ^ tag) | (v0.y ^ tag) | (v0.z ^ tag) | (v0.w ^ tag) | (v1.x ^ tag) | (v1.y ^ tag) | (v1.z ^ tag) | (v1.w ^ tag);
                    if (!__any_sync(~0u, bad & 1u)) break;
                    __nanosleep(50);
                    sp.tick();
                    v0 = ld_relaxed4(src); v1 = ld_relaxed4(src + 128);
                }
#pragma unroll
                for (int s = 0; s < NST; s++) {
                    if (early && s < 3) continue;
                    uint4* dst = reinterpret_cast<uint4*>(sg + s * STAGE + 32768) + lane;
                    dst[0] = v0; dst[32] = v1;
                }
                __syncwarp();
                if (lane < NST && !(early && lane < 3)) mbar_arrive(bar_q + lane * 8);
            }
            if (ctid == 96) TRACE(2);
            if (cw < 2 && cta < NLATE) {
                float acc[4];
                proj32<36>(acc, sb + SM_WBUF, bar_wg, sb + SM_XN, lane, cw, 0);
                put_frag(reinterpret_cast<float*>(sg + SM_GL), acc, cw, lane >> 2, lane & 3);
                __syncwarp();
                if (lane == 0) mbar_arrive(bar_gdone);
            }
        }
        if (cta < 128) {
            const int g = lane >> 2, t = lane & 3;
            const int hkv = cta >> 3, head = (cta >> 2) & 1, qd = cta & 3;
            uint32_t* sdst = g_sp + (hkv * NB + 2 * t) * DM + (cta & 7) * 72 + cw * 16 + g;
            const uint4* oxs = g_ox + (hkv * 8 * NB + g) * 8 + t;
            uint32_t ob[16][2];
            auto collect_o = [&](bool on) {
                uint4 v[16];
                Spin sp;
                while (true) {
                    uint32_t bad = 0;
                    if (on) {
#pragma unroll
                        for (int i = 0; i < 16; i++) v[i] = ld_relaxed4(oxs + (i >> 1) * (NB * 8) + (i & 1) * 4);
#pragma unroll
                        for (int i = 0; i < 16; i++) bad |= bad4(v[i], tag);
                    }
                    if (!__any_sync(~0u, bad)) break;
                    __nanosleep(PSLEEP);
                    sp.tick();
                }
                if (on) {
#pragma unroll
                    for (int i = 0; i < 16; i++) { ob[i][0] = __byte_perm(v[i].x, v[i].y, 0x7632); ob[i][1] = __byte_perm(v[i].z, v[i].w, 0x7632); }
                }
            };
#pragma unroll 1
            for (int b = 0; b < NB; b++) {
                const int p = b * HKV + hkv;
                uint2 e;
                uint4 v[4];
                const uint2* rows = g_po + ((size_t)((p * 2 + head) * 4 + qd) * TPP + cw * 32 + g) * 8 + t * 2;
                {
                    const uint2* mlp = reinterpret_cast<const uint2*>(g_ml + (p * TPP + cw * 32 + lane) * 2) + head;
                    Spin sp;
                    const int plast = p < NPLAIN ? (p + 1) * (TPP - NST) : NDYN1 + (p - NPLAIN + 1) * TPP;
                    const int target = min(plast + MARGIN, NDYN - TAILPOLL);
                    while (desc[9] < target) { __nanosleep(250); sp.tick(); }
                    if (b == NB - 1) collect_o(g < NB - 1);
                    while (true) {
                        e = ld_relaxed2(mlp);
                        const uint32_t miss = __ballot_sync(~0u, ((e.x ^ tag) | (e.y ^ tag)) & 1u);
                        if (!miss) break;
                        __nanosleep(miss == ~0u ? LAZY : TIGHT);
                        sp.tick();
                    }
                }
                if (b == TRB && ctid == 96) TRACE(10);
#pragma unroll
                for (int i = 0; i < 4; i++) v[i] = ld_relaxed4(rows + i * 64);
                const float m = untagf(e.x);
                float M = m;
#pragma unroll
                for (int o = 16; o; o >>= 1) M = fmaxf(M, __shfl_xor_sync(~0u, M, o));
                const float w = ex2(m - M) * untagf(e.y);
                float L = w;
#pragma unroll
                for (int o = 16; o; o >>= 1) L += __shfl_xor_sync(~0u, L, o);
                float wr[4];
#pragma unroll
                for (int i = 0; i < 4; i++) wr[i] = __shfl_sync(~0u, w, i * 8 + g);
                {
                    Spin sp;
                    while (__any_sync(~0u, bad4(v[0], tag) | bad4(v[1], tag) | bad4(v[2], tag) | bad4(v[3], tag))) {
#pragma unroll
                        for (int i = 0; i < 4; i++) v[i] = ld_relaxed4(rows + i * 64);
                        sp.tick();
                    }
                }
                if (b == TRB && ctid == 96) TRACE(11);
                float acc[8];
#pragma unroll
                for (int k = 0; k < 8; k++) acc[k] = 0.f;
#pragma unroll
                for (int i = 0; i < 4; i++) {
                    const uint32_t u[4] = {v[i].x, v[i].y, v[i].z, v[i].w};
#pragma unroll
                    for (int k = 0; k < 4; k++) {
                        acc[2 * k] = fmaf(wr[i], __uint_as_float((u[k] << 16) & 0xFFFE0000u), acc[2 * k]);
                        acc[2 * k + 1] = fmaf(wr[i], __uint_as_float(u[k] & 0xFFFF0000u), acc[2 * k + 1]);
                    }
                }
#pragma unroll
                for (int k = 0; k < 8; k++) {
                    acc[k] += __shfl_xor_sync(~0u, acc[k], 4);
                    acc[k] += __shfl_xor_sync(~0u, acc[k], 8);
                    acc[k] += __shfl_xor_sync(~0u, acc[k], 16);
                }
                float* part = reinterpret_cast<float*>(sg + SM_PART) + (b & 1) * 160;
                if (g == 0) {
#pragma unroll
                    for (int k = 0; k < 4; k++) *reinterpret_cast<float2*>(part + cw * 40 + k * 8 + 2 * t) = make_float2(acc[k], acc[k + 4]);
                    if (t == 0) *reinterpret_cast<float2*>(part + cw * 40 + 32) = make_float2(M, L);
                }
                bar_comb();
                if (ctid < 8) {
                    float2 ml4[4];
#pragma unroll
                    for (int i = 0; i < 4; i++) ml4[i] = *reinterpret_cast<const float2*>(part + i * 40 + 32);
                    const float MM = fmaxf(fmaxf(ml4[0].x, ml4[1].x), fmaxf(ml4[2].x, ml4[3].x));
                    float sw[4], LL = 0.f;
#pragma unroll
                    for (int i = 0; i < 4; i++) { sw[i] = ex2(ml4[i].x - MM); LL = fmaf(sw[i], ml4[i].y, LL); }
                    const float inv = 1.0f / LL;
                    uint32_t pk[2];
#pragma unroll
                    for (int j = 0; j < 2; j++) {
                        float o0 = 0.f, o1 = 0.f;
#pragma unroll
                        for (int i = 0; i < 4; i++) {
                            const float2 pv = *reinterpret_cast<const float2*>(part + i * 40 + g * 16 + j * 8 + 2 * t);
                            o0 = fmaf(sw[i], pv.x, o0); o1 = fmaf(sw[i], pv.y, o1);
                        }
                        pk[j] = pack_bf16(o0 * inv, o1 * inv);
                    }
                    uint4* dst = g_ox + (cta * NB + b) * 8 + ctid;
                    st_relaxed4(dst, (pk[0] << 16) | tag, (pk[0] & 0xFFFF0000u) | tag, (pk[1] << 16) | tag, (pk[1] & 0xFFFF0000u) | tag);
                    if (b == NB - 2) st_relaxed4(dst + 8, tag ^ 1u, tag ^ 1u, tag ^ 1u, tag ^ 1u);
                }
                if (b == NB - 2) {
                    const uint32_t inv = tag ^ 1u;
                    put_tile(sdst, inv, inv, inv, inv, true);
                    if (cw == 0) put_tile(sdst + 64, inv, inv, inv, inv, false);
                }
                __syncwarp();
                if (b == TRB && ctid == 0) TRACE(13);
            }
            if (ODELAY) __nanosleep(ODELAY);
            collect_o(g == NB - 1);
            if (ctid == 0) TRACE(12);
#pragma unroll
            for (int i = 0; i < 4; i++) mbar_wait(bar_wo + i * 8, 0);
            if (ctid == 0) TRACE(32);
            {
                const int m4 = lane >> 3;
                const uint32_t a0 = sb + SM_WBUF + ((m4 >> 1) * 8 + (lane & 7)) * 144 + (m4 & 1) * 16;
                float c0[4] = {0.f, 0.f, 0.f, 0.f}, c1[4] = {0.f, 0.f, 0.f, 0.f};
                if (cw == 0) {
                    float c2[4] = {0.f, 0.f, 0.f, 0.f}, c3[4] = {0.f, 0.f, 0.f, 0.f};
#pragma unroll
                    for (int ks = 0; ks < 16; ks++) {
                        uint32_t a[4], a2[4];
                        ldsm4t(a, a0 + ks * (16 * 144));
                        ldsm4t(a2, a0 + ks * (16 * 144) + 128);
                        mma16816((ks & 1) ? c1 : c0, a, ob[ks][0], ob[ks][1]);
                        mma16816((ks & 1) ? c3 : c2, a2, ob[ks][0], ob[ks][1]);
                    }
                    put_tile(sdst + 64, tagf(c2[0] + c3[0], tag), tagf(c2[1] + c3[1], tag), 0, 0, false);
                } else {
#pragma unroll
                    for (int ks = 0; ks < 16; ks++) {
                        uint32_t a[4];
                        ldsm4t(a, a0 + ks * (16 * 144) + cw * 32);
                        mma16816((ks & 1) ? c1 : c0, a, ob[ks][0], ob[ks][1]);
                    }
                }
                put_tile(sdst, tagf(c0[0] + c1[0], tag), tagf(c0[1] + c1[1], tag), tagf(c0[2] + c1[2], tag), tagf(c0[3] + c1[3], tag), true);
            }
            if (ctid == 0) TRACE(7);
            gather16(g_sp + cta * 36, reinterpret_cast<float*>(sg + SM_RED) + 144, ctid, tag);
            __syncwarp();
            if (lane == 0) mbar_arrive(bar_ssum);
            if (ctid == 0) TRACE(8);
        }
    }
}

typedef CUresult (*EncodeFn)(CUtensorMap*, CUtensorMapDataType, cuuint32_t, void*, const cuuint64_t*, const cuuint64_t*,
                             const cuuint32_t*, const cuuint32_t*, CUtensorMapInterleave, CUtensorMapSwizzle,
                             CUtensorMapL2promotion, CUtensorMapFloatOOBfill);

void make_map(EncodeFn enc, CUtensorMap* m, const void* p, int rank, const cuuint64_t* dims, const cuuint64_t* strides,
              const cuuint32_t* box, CUtensorMapSwizzle sw, CUtensorMapL2promotion promo) {
    cuuint32_t es[3] = {1, 1, 1};
    enc(m, CU_TENSOR_MAP_DATA_TYPE_BFLOAT16, rank, const_cast<void*>(p), dims, strides, box, es,
        CU_TENSOR_MAP_INTERLEAVE_NONE, sw, promo, CU_TENSOR_MAP_FLOAT_OOB_FILL_NONE);
}

}

extern "C" void kernel_launch(void* const* d_in, const int* in_sizes, int n_in, void* d_out, int out_size) {
    (void)in_sizes; (void)n_in; (void)out_size;
    static EncodeFn enc = nullptr;
    if (!enc) {
        void* fn = nullptr;
        cudaDriverEntryPointQueryResult qr;
        cudaGetDriverEntryPoint("cuTensorMapEncodeTiled", &fn, cudaEnableDefault, &qr);
        enc = (EncodeFn)fn;
        cudaFuncSetAttribute(fused_decode_kernel, cudaFuncAttributeMaxDynamicSharedMemorySize, SMEM_BYTES);
    }
    Maps maps;
    const cuuint64_t kvrows = (cuuint64_t)NPAIR * SK;
    for (int i = 0; i < 2; i++) {
        cuuint64_t dims[3] = {64, kvrows, 2}, strides[2] = {256, 128};
        cuuint32_t box[3] = {64, TILE, 2};
        make_map(enc, i ? &maps.v : &maps.k, d_in[1 + i], 3, dims, strides, box, CU_TENSOR_MAP_SWIZZLE_128B, CU_TENSOR_MAP_L2_PROMOTION_L2_256B);
    }
    {
        cuuint32_t box[2] = {32, 192};
        cuuint64_t dq[2] = {4096, DM}, sq[1] = {4096 * 2};
        make_map(enc, &maps.wq, d_in[3], 2, dq, sq, box, CU_TENSOR_MAP_SWIZZLE_64B, CU_TENSOR_MAP_L2_PROMOTION_L2_128B);
        cuuint64_t df[2] = {FF, DM}, sf[1] = {FF * 2};
        make_map(enc, &maps.wg, d_in[6], 2, df, sf, box, CU_TENSOR_MAP_SWIZZLE_64B, CU_TENSOR_MAP_L2_PROMOTION_L2_128B);
        make_map(enc, &maps.wu, d_in[7], 2, df, sf, box, CU_TENSOR_MAP_SWIZZLE_64B, CU_TENSOR_MAP_L2_PROMOTION_L2_128B);
    }
    {
        cuuint32_t boxo[2] = {72, 64};
        cuuint64_t d_o[2] = {DM, 4096}, s_o[1] = {DM * 2};
        make_map(enc, &maps.wo, d_in[4], 2, d_o, s_o, boxo, CU_TENSOR_MAP_SWIZZLE_NONE, CU_TENSOR_MAP_L2_PROMOTION_L2_128B);
        cuuint32_t boxd[2] = {64, 96};
        cuuint64_t d_d[2] = {DM, FF}, s_d[1] = {DM * 2};
        make_map(enc, &maps.wd, d_in[8], 2, d_d, s_d, boxd, CU_TENSOR_MAP_SWIZZLE_128B, CU_TENSOR_MAP_L2_PROMOTION_L2_128B);
    }
    fused_decode_kernel<<<NCTA, NTHREADS, SMEM_BYTES>>>(maps, (const __nv_bfloat16*)d_in[0], (__nv_bfloat16*)d_out);
}
```

```cpp
#include <cuda_runtime.h>
#include <cuda_bf16.h>
#include <cuda.h>
#include <math.h>
#include <stdint.h>

namespace {

constexpr int NB = 8, DM = 576, HKV = 16, SK = 8192, FF = 4608;
constexpr int NPAIR = NB * HKV;
constexpr int TILE = 64;
constexpr int TPP = SK / TILE;
constexpr int NKV = NPAIR * TPP;
constexpr int NCTA = 132;
constexpr int NST = 4;
constexpr int STAGE = 36864;
constexpr int NUNIT = FF / 32;
constexpr int GRP = 9;
constexpr int NGRP = NUNIT / GRP;
constexpr int NLATE = (NCTA / GRP) * GRP;
constexpr int NEARLY = NUNIT - NLATE;
constexpr int NPLAIN = NCTA - NEARLY;
constexpr int NDYN = NKV - NPLAIN * NST;
constexpr int XP = 584;
constexpr int NTHREADS = 288;

constexpr int INFLIGHT = 3;
constexpr int SPIECES = 4;
constexpr int EPIECES = 4;
constexpr int LATECLAIM = 400;
constexpr int PEEK = 200;
constexpr int MARGIN = 600;
constexpr int TAILPOLL = 900;
constexpr int QDELAY = 800, HDELAY = 700, ODELAY = 400;

constexpr int SM_WBUF = NST * STAGE;
constexpr int SM_XN = SM_WBUF + STAGE;
constexpr int SM_GU = SM_XN + NB * XP * 2;
constexpr int SM_GL = SM_GU + 2 * 8 * 36 * 4;
constexpr int SM_HB = SM_GL + 8 * 36 * 4;
constexpr int SM_RED = SM_HB + 2 * GRP * 32 * 8;
constexpr int SM_PART = SM_RED + 2 * 4 * 36 * 4;
constexpr int SM_OB = SM_PART + 2 * 4 * 40 * 4;
constexpr int SM_BAR = SM_OB + 4 * 512;
constexpr int NBAR = 4 * NST + 29;
constexpr int SM_DESC = SM_BAR + NBAR * 8;
constexpr int SM_TOTAL = SM_DESC + 64;
constexpr int SMEM_BYTES = SM_TOTAL + 1024;

struct Maps { CUtensorMap k, v, wq, wg, wu, wo, wd; };

__device__ __align__(128) unsigned g_queue[32];
__device__ __align__(128) unsigned g_state[32];
__device__ __align__(128) uint32_t g_q[NPAIR * 256];
__device__ __align__(128) uint4 g_ml[NKV * 2];
__device__ __align__(128) uint2 g_po[NPAIR * 2 * 4 * TPP * 8];
__device__ __align__(128) uint4 g_ox[128 * NB * 8];
__device__ __align__(128) uint32_t g_sp[HKV * NB * DM];
__device__ __align__(128) uint32_t g_fp[NGRP * NB * DM];
__device__ __align__(128) uint4 g_h[NUNIT * 2 * 32];

__device__ __forceinline__ uint32_t s2u(const void* p) { return (uint32_t)__cvta_generic_to_shared(p); }
__device__ __forceinline__ void mbar_init(uint32_t b, int c) { asm volatile("mbarrier.init.shared::cta.b64 [%0], %1;" :: "r"(b), "r"(c)); }
__device__ __forceinline__ void mbar_expect(uint32_t b, uint32_t bytes) { asm volatile("mbarrier.arrive.expect_tx.shared::cta.b64 _, [%0], %1;" :: "r"(b), "r"(bytes) : "memory"); }
__device__ __forceinline__ void mbar_arrive(uint32_t b) { asm volatile("mbarrier.arrive.shared::cta.b64 _, [%0];" :: "r"(b) : "memory"); }
__device__ __forceinline__ bool mbar_try(uint32_t b, uint32_t ph) {
    uint32_t ok;
    asm volatile("{\n.reg .pred p;\nmbarrier.try_wait.parity.shared::cta.b64 p, [%1], %2;\nselp.u32 %0, 1, 0, p;\n}" : "=r"(ok) : "r"(b), "r"(ph) : "memory");
    return ok != 0;
}
__device__ __forceinline__ bool mbar_test(uint32_t b, uint32_t ph) {
    uint32_t ok;
    asm volatile("{\n.reg .pred p;\nmbarrier.test_wait.parity.shared::cta.b64 p, [%1], %2;\nselp.u32 %0, 1, 0, p;\n}" : "=r"(ok) : "r"(b), "r"(ph) : "memory");
    return ok != 0;
}
constexpr long long SPIN_LIMIT = 4000000000LL;
__device__ __forceinline__ void mbar_wait(uint32_t b, uint32_t ph) {
    if (mbar_try(b, ph)) return;
    long long t0 = clock64();
    while (!mbar_try(b, ph)) { if (clock64() - t0 > SPIN_LIMIT) __trap(); }
}
struct Spin {
    long long t0 = 0;
    __device__ __forceinline__ void tick() { long long t = clock64(); if (t0 == 0) t0 = t; else if (t - t0 > SPIN_LIMIT) __trap(); }
};
__device__ __forceinline__ void bulk_g2s(uint32_t dst, const void* src, uint32_t bytes, uint32_t bar) {
    asm volatile("cp.async.bulk.shared::cluster.global.mbarrier::complete_tx::bytes [%0], [%1], %2, [%3];" :: "r"(dst), "l"(src), "r"(bytes), "r"(bar) : "memory");
}
__device__ __forceinline__ void tma2d(uint32_t dst, const CUtensorMap* m, int c0, int c1, uint32_t bar) {
    asm volatile("cp.async.bulk.tensor.2d.shared::cluster.global.mbarrier::complete_tx::bytes [%0], [%1, {%3, %4}], [%2];" :: "r"(dst), "l"(m), "r"(bar), "r"(c0), "r"(c1) : "memory");
}
__device__ __forceinline__ void tma3d(uint32_t dst, const CUtensorMap* m, int c0, int c1, int c2, uint32_t bar, uint64_t pol) {
    asm volatile("cp.async.bulk.tensor.3d.shared::cluster.global.mbarrier::complete_tx::bytes.L2::cache_hint [%0], [%1, {%3, %4, %5}], [%2], %6;" :: "r"(dst), "l"(m), "r"(bar), "r"(c0), "r"(c1), "r"(c2), "l"(pol) : "memory");
}
__device__ __forceinline__ void ldsm4(uint32_t (&r)[4], uint32_t a) {
    asm volatile("ldmatrix.sync.aligned.m8n8.x4.shared.b16 {%0,%1,%2,%3}, [%4];" : "=r"(r[0]), "=r"(r[1]), "=r"(r[2]), "=r"(r[3]) : "r"(a));
}
__device__ __forceinline__ void ldsm4t(uint32_t (&r)[4], uint32_t a) {
    asm volatile("ldmatrix.sync.aligned.m8n8.x4.trans.shared.b16 {%0,%1,%2,%3}, [%4];" : "=r"(r[0]), "=r"(r[1]), "=r"(r[2]), "=r"(r[3]) : "r"(a));
}
__device__ __forceinline__ void mma16816(float (&c)[4], const uint32_t (&a)[4], uint32_t b0, uint32_t b1) {
    asm("mma.sync.aligned.m16n8k16.row.col.f32.bf16.bf16.f32 {%0,%1,%2,%3}, {%4,%5,%6,%7}, {%8,%9}, {%0,%1,%2,%3};"
                 : "+f"(c[0]), "+f"(c[1]), "+f"(c[2]), "+f"(c[3]) : "r"(a[0]), "r"(a[1]), "r"(a[2]), "r"(a[3]), "r"(b0), "r"(b1));
}
__device__ __forceinline__ uint4 ld_relaxed4(const void* p) {
    uint4 v; asm volatile("ld.relaxed.gpu.global.v4.u32 {%0,%1,%2,%3}, [%4];" : "=r"(v.x), "=r"(v.y), "=r"(v.z), "=r"(v.w) : "l"(p) : "memory"); return v;
}
__device__ __forceinline__ uint2 ld_relaxed2(const void* p) {
    uint2 v; asm volatile("ld.relaxed.gpu.global.v2.u32 {%0,%1}, [%2];" : "=r"(v.x), "=r"(v.y) : "l"(p) : "memory"); return v;
}
__device__ __forceinline__ uint32_t ld_relaxed1(const void* p) {
    uint32_t v; asm volatile("ld.relaxed.gpu.global.u32 %0, [%1];" : "=r"(v) : "l"(p) : "memory"); return v;
}
__device__ __forceinline__ void st_relaxed4(void* p, uint32_t a, uint32_t b, uint32_t c, uint32_t d) {
    asm volatile("st.relaxed.gpu.global.v4.u32 [%0], {%1,%2,%3,%4};" :: "l"(p), "r"(a), "r"(b), "r"(c), "r"(d) : "memory");
}
__device__ __forceinline__ void st_relaxed1(void* p, uint32_t a) {
    asm volatile("st.relaxed.gpu.global.u32 [%0], %1;" :: "l"(p), "r"(a) : "memory");
}
__device__ __forceinline__ void st_relaxed2(void* p, uint32_t a, uint32_t b) {
    asm volatile("st.relaxed.gpu.global.v2.u32 [%0], {%1,%2};" :: "l"(p), "r"(a), "r"(b) : "memory");
}
__device__ __forceinline__ uint4 lds128(uint32_t a) { uint4 v; asm volatile("ld.shared.v4.u32 {%0,%1,%2,%3}, [%4];" : "=r"(v.x), "=r"(v.y), "=r"(v.z), "=r"(v.w) : "r"(a) : "memory"); return v; }
__device__ __forceinline__ void bar_cons() { asm volatile("bar.sync 1, 128;" ::: "memory"); }
__device__ __forceinline__ void bar_comb() { asm volatile("bar.sync 2, 128;" ::: "memory"); }
__device__ __forceinline__ float bfr(float v) { return __bfloat162float(__float2bfloat16_rn(v)); }
__device__ __forceinline__ uint32_t pack_bf16(float lo, float hi) {
    uint32_t r; asm("cvt.rn.bf16x2.f32 %0, %1, %2;" : "=r"(r) : "f"(hi), "f"(lo)); return r;
}
__device__ __forceinline__ float ex2(float x) { float y; asm("ex2.approx.ftz.f32 %0, %1;" : "=f"(y) : "f"(x)); return y; }
__device__ __forceinline__ float silu_f(float v) { return __fdividef(v, 1.0f + __expf(-v)); }
__device__ __forceinline__ uint32_t tagf(float v, uint32_t tag) { return (__float_as_uint(v) & ~1u) | tag; }
__device__ __forceinline__ float untagf(uint32_t w) { return __uint_as_float(w & ~1u); }
__device__ __forceinline__ uint32_t bad4(const uint4& v, uint32_t tag) { return ((v.x ^ tag) | (v.y ^ tag) | (v.z ^ tag) | (v.w ^ tag)) & 1u; }
__device__ __forceinline__ uint32_t pack_tag(float lo, float hi, uint32_t tag) {
    uint32_t l = ((__float_as_uint(lo) + 0x10000u) >> 16) & 0xFFFEu;
    uint32_t h = pack_bf16(0.f, hi) & 0xFFFF0000u;
    return h | l | tag;
}

__device__ __forceinline__ int dyn_tile(int n) { return n + NPLAIN * NST; }

__device__ __forceinline__ uint32_t addr_w32(uint32_t base, int lane, int mt, int ks) {
    int mat = lane >> 3, row = ks * 16 + (mat >> 1) * 8 + (lane & 7), c = mt * 2 + (mat & 1);
    return base + row * 64 + ((c ^ ((row >> 1) & 3)) << 4);
}
__device__ __forceinline__ uint32_t addr_kv(uint32_t base, int key, int chunk) {
    return base + (chunk >> 3) * 8192 + key * 128 + (((chunk & 7) ^ (key & 7)) << 4);
}

template <int NKS>
__device__ __forceinline__ void proj32(float (&acc)[4], uint32_t wbase, uint32_t bar, uint32_t xn, int lane, int mt, int ks0) {
    uint32_t xb[NKS / 2][4];
    const uint32_t xa = xn + ((lane & 7) * XP + (lane >> 3) * 8 + ks0 * 16) * 2;
#pragma unroll
    for (int i = 0; i < NKS / 2; i++) ldsm4(xb[i], xa + i * 64);
    float a4[4][4];
#pragma unroll
    for (int i = 0; i < 4; i++) { a4[i][0] = a4[i][1] = a4[i][2] = a4[i][3] = 0.f; }
    const uint32_t wa = addr_w32(wbase, lane, mt, ks0);
    if (ks0 < 12) mbar_wait(bar, 0);
    mbar_wait(bar + 8, 0);
    if (ks0 + NKS > 24) mbar_wait(bar + 16, 0);
#pragma unroll
    for (int i = 0; i < NKS; i++) {
        uint32_t a[4];
        ldsm4t(a, wa + i * 1024);
        mma16816(a4[i & 3], a, xb[i >> 1][(i & 1) * 2], xb[i >> 1][(i & 1) * 2 + 1]);
    }
#pragma unroll
    for (int i = 0; i < 4; i++) acc[i] = (a4[0][i] + a4[1][i]) + (a4[2][i] + a4[3][i]);
}

__device__ __forceinline__ void put_frag(float* dst, const float (&acc)[4], int mt, int g, int t) {
    dst[(2 * t) * 36 + mt * 16 + g] = acc[0];
    dst[(2 * t + 1) * 36 + mt * 16 + g] = acc[1];
    dst[(2 * t) * 36 + mt * 16 + g + 8] = acc[2];
    dst[(2 * t + 1) * 36 + mt * 16 + g + 8] = acc[3];
}
__device__ __forceinline__ void put_tile(uint32_t* dst, uint32_t w0, uint32_t w1, uint32_t w2, uint32_t w3, bool upper) {
    st_relaxed1(dst, w0); st_relaxed1(dst + DM, w1);
    if (upper) { st_relaxed1(dst + 8, w2); st_relaxed1(dst + DM + 8, w3); }
}
__device__ __forceinline__ uint32_t* fp_slot(int unit, int warp, int g, int t) {
    return g_fp + ((unit / GRP) * NB + 2 * t) * DM + (unit % GRP) * 64 + warp * 16 + g;
}

template <bool LATE>
__device__ __forceinline__ void ffn_unit(uint32_t sb, uint32_t bufG, uint32_t bufU, uint32_t bufD, uint32_t barG, uint32_t barU,
                                         uint32_t barD, int unit, int warp, int lane, uint32_t tag) {
    const int g = lane >> 2, t = lane & 3;
    const int hf = warp >> 1, mt = warp & 1;
    float* gu = reinterpret_cast<float*>(__cvta_shared_to_generic(sb + SM_GU));
    float acc[4];
    if (LATE) { mbar_wait(barG, 0); proj32<18>(acc, bufU, barU, sb + SM_XN, lane, mt, hf * 18); }
    else proj32<36>(acc, hf ? bufU : bufG, hf ? barU : barG, sb + SM_XN, lane, mt, 0);
    put_frag(gu + hf * 288, acc, mt, g, t);
    bar_cons();
    if (warp < 2) {
        uint32_t hw[2];
#pragma unroll
        for (int j = 0; j < 2; j++) {
            const int f = g * 36 + warp * 16 + j * 8 + 2 * t;
            const float2 p0 = *reinterpret_cast<const float2*>(gu + f), p1 = *reinterpret_cast<const float2*>(gu + 288 + f);
            float2 gg = p0, uu = p1;
            if (LATE) { gg = *reinterpret_cast<const float2*>(gu + 576 + f); uu = make_float2(p0.x + p1.x, p0.y + p1.y); }
            hw[j] = pack_bf16(bfr(silu_f(bfr(gg.x))) * bfr(uu.x), bfr(silu_f(bfr(gg.y))) * bfr(uu.y));
        }
        st_relaxed4(g_h + (unit * 2 + warp) * 32 + lane, (hw[0] << 16) | tag, (hw[0] & 0xFFFF0000u) | tag, (hw[1] << 16) | tag, (hw[1] & 0xFFFF0000u) | tag);
    }
    {
        const uint4* src = g_h + (unit / GRP) * (2 * GRP * 32) + warp * 32 + lane;
        uint4 v[5];
        uint32_t pend = warp < 2 ? 0x1Fu : 0xFu;
        Spin sp;
        if (LATE) __nanosleep(HDELAY);
        while (true) {
#pragma unroll
            for (int i = 0; i < 5; i++)
                if (pend >> i & 1) v[i] = ld_relaxed4(src + i * 128);
#pragma unroll
            for (int i = 0; i < 5; i++)
                if ((pend >> i & 1) && !__any_sync(~0u, bad4(v[i], tag))) {
                    pend &= ~(1u << i);
                    asm volatile("st.shared.v2.u32 [%0], {%1, %2};" :: "r"(sb + SM_HB + ((i * 4 + warp) * 32 + lane) * 8),
                                 "r"(__byte_perm(v[i].x, v[i].y, 0x7632)), "r"(__byte_perm(v[i].z, v[i].w, 0x7632)) : "memory");
                }
            if (!pend) break;
            __nanosleep(30);
            sp.tick();
        }
    }
    mbar_wait(barD, 0); mbar_wait(barD + 8, 0); mbar_wait(barD + 16, 0);
    uint32_t a[2 * GRP][4];
    {
        const int m4 = lane >> 3, row = (m4 >> 1) * 8 + (lane & 7), c = warp * 2 + (m4 & 1);
        const uint32_t a0 = bufD + row * 128 + ((c ^ (lane & 7)) << 4);
#pragma unroll
        for (int ks = 0; ks < 2 * GRP; ks++) ldsm4t(a[ks], a0 + ks * 2048);
    }
    bar_cons();
    float c0[4] = {0.f, 0.f, 0.f, 0.f}, c1[4] = {0.f, 0.f, 0.f, 0.f}, c2[4] = {0.f, 0.f, 0.f, 0.f};
#pragma unroll
    for (int ks = 0; ks < 2 * GRP; ks++) {
        uint32_t h0, h1;
        asm volatile("ld.shared.v2.u32 {%0, %1}, [%2];" : "=r"(h0), "=r"(h1) : "r"(sb + SM_HB + (ks * 32 + lane) * 8) : "memory");
        mma16816(ks % 3 == 0 ? c0 : ks % 3 == 1 ? c1 : c2, a[ks], h0, h1);
    }
    put_tile(fp_slot(unit, warp, g, t), tagf(c0[0] + c1[0] + c2[0], tag), tagf(c0[1] + c1[1] + c2[1], tag),
             tagf(c0[2] + c1[2] + c2[2], tag), tagf(c0[3] + c1[3] + c2[3], tag), true);
}

__device__ __forceinline__ void gather16(const uint32_t* base, float* red, int tid, uint32_t tag) {
    const int f = tid & 7;
    const uint32_t* src = base + (tid >> 3) * (NB * DM) + f * 4;
    uint4 v0, v1 = make_uint4(tag, tag, tag, tag);
    Spin sp;
    while (true) {
        v0 = ld_relaxed4(src);
        if (f == 0) v1 = ld_relaxed4(src + 32);
        if (!__any_sync(~0u, bad4(v0, tag) | bad4(v1, tag))) break;
        __nanosleep(30);
        sp.tick();
    }
    float a[8] = {untagf(v0.x), untagf(v0.y), untagf(v0.z), untagf(v0.w), untagf(v1.x), untagf(v1.y), untagf(v1.z), untagf(v1.w)};
#pragma unroll
    for (int i = 0; i < 8; i++) { a[i] += __shfl_xor_sync(~0u, a[i], 8); a[i] += __shfl_xor_sync(~0u, a[i], 16); }
    if ((tid & 31) < 8) {
        float* r = red + (tid >> 5) * 36;
        *reinterpret_cast<float4*>(r + f * 4) = make_float4(a[0], a[1], a[2], a[3]);
        if (f == 0) *reinterpret_cast<float4*>(r + 32) = make_float4(a[4], a[5], a[6], a[7]);
    }
}

__global__ void __launch_bounds__(NTHREADS, 1)
fused_decode_kernel(const __grid_constant__ Maps maps, const __nv_bfloat16* __restrict__ x, __nv_bfloat16* __restrict__ out) {
    extern __shared__ uint8_t smem_raw[];
    const uint32_t sb = (s2u(smem_raw) + 1023u) & ~1023u;
    uint8_t* sg = smem_raw + (sb - s2u(smem_raw));
    const int tid = threadIdx.x, warp = tid >> 5, lane = tid & 31, cta = blockIdx.x;
    const uint32_t bar_full = sb + SM_BAR, bar_empty = bar_full + NST * 8;
    const uint32_t bar_q = bar_empty + NST * 8, bar_v = bar_q + NST * 8;
    const uint32_t bar_wq = bar_v + NST * 8, bar_wg = bar_wq + 24;
    const uint32_t bar_e = bar_wg + 24;
    const uint32_t bar_lu = bar_e + 72, bar_ld = bar_lu + 24, bar_wo = bar_ld + 24;
    const uint32_t bar_ssum = bar_wo + 32, bar_first = bar_ssum + 8, bar_wfree = bar_first + 8, bar_gdone = bar_wfree + 8;
    volatile int* desc = reinterpret_cast<volatile int*>(sg + SM_DESC);

    uint32_t xr[2][9];
    if (warp < NST) {
#pragma unroll
        for (int r = 0; r < 2; r++)
#pragma unroll
            for (int i = 0; i < 9; i++)
                asm volatile("ld.global.nc.u32 %0, [%1];" : "=r"(xr[r][i]) : "l"(reinterpret_cast<const uint32_t*>(x + (warp * 2 + r) * DM) + i * 32 + lane));
    }
    if (tid >= 160 && tid < 167) asm volatile("prefetch.tensormap [%0];" :: "l"(reinterpret_cast<const CUtensorMap*>(&maps) + (tid - 160)) : "memory");
    uint32_t epoch = 0;
    if (warp != NST) epoch = ld_relaxed1(&g_state[1]);
    if (tid == NST * 32) {
        mbar_init(bar_wq, 1); mbar_init(bar_wq + 8, 1); mbar_init(bar_wq + 16, 1); mbar_init(bar_full, 1); mbar_init(bar_e, 1);
        asm volatile("fence.mbarrier_init.release.cluster;" ::: "memory");
        if (cta < 128) {
#pragma unroll
            for (int i = 0; i < 3; i++) { mbar_expect(bar_wq + i * 8, 12288); tma2d(sb + SM_WBUF + i * 12288, &maps.wq, cta * 32, i * 192, bar_wq + i * 8); }
        }
        if (cta >= NPLAIN) { mbar_expect(bar_e, 12288); tma2d(sb, &maps.wg, (NLATE + cta - NPLAIN) * 32, 0, bar_e); }
        else {
            uint64_t pol; asm volatile("createpolicy.fractional.L2::evict_first.b64 %0, 1.0;" : "=l"(pol));
            mbar_expect(bar_full, 16384);
            tma3d(sb, &maps.k, 0, cta * TILE, 0, bar_full, pol);
        }
    }

    if (warp == NST) {
        uint64_t pol; asm volatile("createpolicy.fractional.L2::evict_first.b64 %0, 1.0;" : "=l"(pol));
        constexpr int FN = 4, F0 = FN - INFLIGHT;
        uint32_t fifo[FN];
#pragma unroll
        for (int i = 0; i < FN; i++) fifo[i] = 0;
        auto gate = [&](int n) { for (int i = F0; i < F0 + n; i++) if (fifo[i]) mbar_wait(fifo[i] & ~1u, fifo[i] & 1u); };
        auto push = [&](uint32_t bar, uint32_t par) {
#pragma unroll
            for (int i = 0; i + 1 < FN; i++) fifo[i] = fifo[i + 1];
            fifo[FN - 1] = bar | par;
        };
        auto issue_half = [&](const CUtensorMap* m, int tile, uint32_t dst, uint32_t bar, uint32_t par) {
            mbar_expect(bar, 16384);
            tma3d(dst, m, 0, tile * TILE, 0, bar, pol);
            push(bar, par);
        };
        auto issue_k = [&](int tile, int st, uint32_t par) { desc[st] = tile; issue_half(&maps.k, tile, sb + st * STAGE, bar_full + st * 8, par); };
        auto issue_v = [&](int tile, int st, uint32_t par) { issue_half(&maps.v, tile, sb + st * STAGE + 16384, bar_v + st * 8, par); };
        auto piece = [&](const CUtensorMap* m, int c0, int c1, uint32_t dst, uint32_t bar, uint32_t bytes) {
            mbar_expect(bar, bytes);
            tma2d(dst, m, c0, c1, bar);
            push(bar, 0);
        };
        auto col_piece = [&](const CUtensorMap* m, int unit, int i, uint32_t buf, uint32_t bar) { piece(m, unit * 32, i * 192, buf + i * 12288, bar + i * 8, 12288); };
        auto down_piece = [&](int unit, int i, uint32_t buf, uint32_t bar) {
            piece(&maps.wd, (unit % GRP) * 64, (unit / GRP) * (GRP * 32) + i * 96, buf + i * 12288, bar + i * 8, 12288);
        };
        auto gate4 = [&]() { const uint32_t f = fifo[FN - SPIECES]; if (f) mbar_wait(f & ~1u, f & 1u); };
        const bool early = cta >= NPLAIN;
        const int eunit = NLATE + cta - NPLAIN;
        int next = 0;
        auto claim = [&]() { return (int)atomicAdd(&g_queue[0], 1u); };
        if (lane == 0) {
            if (cta < 128) for (int i = 0; i < 3; i++) push(bar_wq + i * 8, 0);
            push(early ? bar_e : bar_full, 0);
            next = claim();
            desc[0] = cta; desc[9] = 0;
#pragma unroll
            for (int i = 1; i < NBAR; i++) {
                const int o = i * 8;
                if (o >= 4 * NST * 8 && o < 4 * NST * 8 + 24) continue;
                if (o == 4 * NST * 8 + 48) continue;
                mbar_init(bar_full + o, bar_full + o == bar_ssum ? 4 : bar_full + o == bar_gdone ? 2 : 1);
            }
            asm volatile("fence.mbarrier_init.release.cluster;" ::: "memory");
        }
        __syncwarp();
        asm volatile("bar.arrive 0, %0;" :: "n"(NTHREADS) : "memory");
        if (lane == 0) {
            if (early) {
                for (int i = 1; i < 3; i++) { gate4(); col_piece(&maps.wg, eunit, i, sb, bar_e); }
                for (int i = 0; i < 3; i++) { gate4(); col_piece(&maps.wu, eunit, i, sb + STAGE, bar_e + 24); }
                for (int i = 0; i < 3; i++) { gate4(); down_piece(eunit, i, sb + 2 * STAGE, bar_e + 48); }
                const int tile = dyn_tile(next);
                gate4(); issue_k(tile, 3, 0); mbar_arrive(bar_first);
                next = claim();
                gate4(); issue_v(tile, 3, 0);
            } else {
                gate4(); issue_v(cta, 0, 0);
#pragma unroll
                for (int i = 1; i < NST; i++) { gate4(); issue_k(cta + i * NPLAIN, i, 0); gate4(); issue_v(cta + i * NPLAIN, i, 0); }
            }
            if (cta < 128) mbar_wait(bar_wfree, 0);
            if (cta < NLATE) for (int i = 0; i < 3; i++) { gate4(); col_piece(&maps.wg, cta, i, sb + SM_WBUF, bar_wg); }
            if (early) mbar_wait(bar_q + 24, 0);
            int st = 0; uint32_t ph = 0;
            while (true) {
                if (next < 0) {
                    Spin sp;
                    while (!mbar_test(fifo[F0] & ~1u, fifo[F0] & 1u)) {
                        if (desc[9] >= NDYN - PEEK && ld_relaxed1(&g_queue[0]) >= (unsigned)NDYN) { next = NDYN; break; }
                        __nanosleep(100);
                        sp.tick();
                    }
                    if (next >= NDYN) break;
                    mbar_wait(bar_empty + st * 8, ph);
                    next = claim();
                } else {
                    gate(1);
                    mbar_wait(bar_empty + st * 8, ph);
                }
                if (next >= NDYN) break;
                const int tile = dyn_tile(next);
                const uint32_t par = (early && st < 3) ? ph : ph ^ 1u;
                issue_k(tile, st, par);
                desc[9] = next;
                mbar_expect(bar_q + st * 8, 1024);
                bulk_g2s(sb + st * STAGE + 32768, g_q + (tile / TPP) * 256, 1024, bar_q + st * 8);
                next = next >= NDYN - LATECLAIM ? -1 : claim();
                if (next >= 0) gate(1);
                issue_v(tile, st, par);
                if (++st == NST) { st = 0; ph ^= 1; }
            }
            desc[9] = NDYN;
            const int stU = st;
            desc[4] = stU;
#pragma unroll
            for (int i = 0; i < F0; i++) fifo[i] = 0;
            int ends = 0, k = cta < NLATE ? 0 : 6;
            const int kend = cta < 128 ? 10 : 6;
            if (cta < NLATE) mbar_wait(bar_gdone, 0);
            Spin sp;
            while (ends < NST || k < kend) {
                if (ends < NST && mbar_test(bar_empty + st * 8, ph)) {
#pragma unroll
                    for (int i = 0; i < FN; i++) if ((fifo[i] & ~1u) == bar_full + st * 8) fifo[i] = 0;
                    desc[st] = -1;
                    mbar_arrive(bar_full + st * 8);
                    if (++st == NST) { st = 0; ph ^= 1; }
                    ends++;
                }
                const uint32_t f = fifo[FN - EPIECES];
                if (k < kend && ends >= (k < 3 ? 1 : k < 6 ? 2 : 0) && (f == 0 || mbar_test(f & ~1u, f & 1u))) {
                    if (k < 3) col_piece(&maps.wu, cta, k, sb + stU * STAGE, bar_lu);
                    else if (k < 6) down_piece(cta, k - 3, sb + ((stU + 1) % NST) * STAGE, bar_ld);
                    else piece(&maps.wo, (cta & 7) * 72, (cta >> 3) * 256 + (k - 6) * 64, sb + SM_WBUF + (k - 6) * 9216, bar_wo + (k - 6) * 8, 9216);
                    k++;
                }
                sp.tick();
            }
            if (atomicAdd(&g_state[0], 1u) == NCTA - 1) {
                g_queue[0] = 0; g_state[0] = 0;
                g_state[1] = g_state[1] + 1;
            }
        }
    } else if (warp < NST) {
        const int g = lane >> 2, t = lane & 3;
        float xfin = 0.f;
        if (tid < 36 && cta < 128) xfin = __bfloat162float(x[cta * 36 + tid]);
        {
#pragma unroll
            for (int r = 0; r < 2; r++) {
                float v[18], s = 0.f;
#pragma unroll
                for (int i = 0; i < 9; i++) { v[2 * i] = __uint_as_float(xr[r][i] << 16); v[2 * i + 1] = __uint_as_float(xr[r][i] & 0xFFFF0000u); s += v[2 * i] + v[2 * i + 1]; }
#pragma unroll
                for (int o = 16; o; o >>= 1) s += __shfl_xor_sync(~0u, s, o);
                const float mean = s * (1.0f / DM);
                float q = 0.f;
#pragma unroll
                for (int i = 0; i < 18; i++) { float d = v[i] - mean; q += d * d; }
#pragma unroll
                for (int o = 16; o; o >>= 1) q += __shfl_xor_sync(~0u, q, o);
                const float mb = bfr(mean), rden = __frcp_rn(bfr(__fsqrt_rn(bfr(bfr(q * (1.0f / DM)) + 1e-5f))));
                uint32_t* xn = reinterpret_cast<uint32_t*>(sg + SM_XN) + (warp * 2 + r) * (XP / 2);
#pragma unroll
                for (int i = 0; i < 9; i++) xn[i * 32 + lane] = pack_bf16(bfr(v[2 * i] - mb) * rden, bfr(v[2 * i + 1] - mb) * rden);
            }
        }
        const uint32_t tag = (epoch & 1u) ^ 1u;
        asm volatile("bar.sync 0, %0;" :: "n"(NTHREADS), "r"(tag) : "memory");
        if (cta < 128) {
            float acc[4];
            const int mt = warp & 1, kh = warp >> 1;
            proj32<18>(acc, sb + SM_WBUF, bar_wq, sb + SM_XN, lane, mt, kh * 18);
            float* gu = reinterpret_cast<float*>(sg + SM_GU);
            put_frag(gu + kh * 288, acc, mt, g, t);
            bar_cons();
            {
                const int b = tid >> 4, c = (tid & 15) * 2;
                const float q0 = gu[b * 36 + c] + gu[(8 + b) * 36 + c], q1 = gu[b * 36 + c + 1] + gu[(8 + b) * 36 + c + 1];
                const int hq = cta >> 2, d = (cta & 3) * 32 + c;
                const int off = (b * HKV + (hq >> 1)) * 256 + (hq & 1) * 128 + (d >> 4) * 16 + ((d & 7) >> 1) * 4 + ((d >> 3) & 1) * 2;
                const uint32_t pk = pack_bf16(q0, q1);
                st_relaxed2(g_q + off, (pk << 16) | tag, (pk & 0xFFFF0000u) | tag);
            }
            bar_cons();
            if (tid == 0) mbar_arrive(bar_wfree);
        }
        if (cta >= NPLAIN) {
            ffn_unit<false>(sb, sb, sb + STAGE, sb + 2 * STAGE, bar_e, bar_e + 24, bar_e + 48, NLATE + cta - NPLAIN, warp, lane, tag);
            bar_cons();
            if (warp < 3 && lane == 0) mbar_arrive(bar_empty + warp * 8);
        }
        const uint32_t kb = sb + warp * STAGE, vb = kb + 16384, qb = kb + 32768;
        const int mat = lane >> 3, r8 = lane & 7;
        const int kkey = (mat & 1) ? 8 + ((r8 + 4) & 7) : r8;
        const int rho = (r8 >> 1) + (mat >> 1) * 4;
        const int vkey = (r8 & 1) ? 8 + ((rho + 4) & 7) : rho;
        const float sc = 0.08838834764831845f * 1.4426950408889634f;
        uint32_t ph = 0;
        while (true) {
            mbar_wait(bar_full + warp * 8, ph);
            ph ^= 1;
            const int tile = desc[warp];
            if (tile < 0) break;
            mbar_wait(bar_q + warp * 8, ph ^ 1u);
            uint32_t qf[16];
            {
                const bool on = (g == 0) || (g == 2);
                uint4 v[8];
                uint32_t bad = 0;
#pragma unroll
                for (int j = 0; j < 8; j++) {
                    v[j] = make_uint4(tag, tag, tag, tag);
                    if (on) v[j] = lds128(qb + (g >> 1) * 512 + j * 64 + t * 16);
                    bad |= (v[j].x ^ tag) | (v[j].y ^ tag) | (v[j].z ^ tag) | (v[j].w ^ tag);
                }
                if (__any_sync(~0u, bad & 1u)) {
                    Spin sp;
                    do {
                        bad = 0;
                        if (on) {
#pragma unroll
                            for (int j = 0; j < 8; j++) v[j] = ld_relaxed4(g_q + (tile / TPP) * 256 + (g >> 1) * 128 + j * 16 + t * 4);
#pragma unroll
                            for (int j = 0; j < 8; j++) bad |= bad4(v[j], tag);
                        }
                        sp.tick();
                    } while (__any_sync(~0u, bad));
                }
#pragma unroll
                for (int j = 0; j < 8; j++) { qf[2 * j] = __byte_perm(v[j].x, v[j].y, 0x7632); qf[2 * j + 1] = __byte_perm(v[j].z, v[j].w, 0x7632); }
            }
            float s[4][4];
#pragma unroll
            for (int mt = 0; mt < 4; mt++) { s[mt][0] = s[mt][1] = s[mt][2] = s[mt][3] = 0.f; }
#pragma unroll
            for (int ks = 0; ks < 8; ks++)
#pragma unroll
                for (int mt = 0; mt < 4; mt++) {
                    uint32_t a[4];
                    ldsm4(a, addr_kv(kb, mt * 16 + kkey, 2 * ks + (mat >> 1)));
                    mma16816(s[mt], a, qf[2 * ks], qf[2 * ks + 1]);
                }
            float m = fmaxf(fmaxf(fmaxf(s[0][0], s[0][2]), fmaxf(s[1][0], s[1][2])), fmaxf(fmaxf(s[2][0], s[2][2]), fmaxf(s[3][0], s[3][2])));
            m = fmaxf(m, __shfl_xor_sync(~0u, m, 4));
            m = fmaxf(m, __shfl_xor_sync(~0u, m, 8));
            m = fmaxf(m, __shfl_xor_sync(~0u, m, 16));
            const float ms = untagf(__float_as_uint(m * sc));
            float l = 0.f;
            uint32_t pb[4][2];
#pragma unroll
            for (int mt = 0; mt < 4; mt++) {
                const float p0 = ex2(fmaf(s[mt][0], sc, -ms)), p1 = ex2(fmaf(s[mt][2], sc, -ms));
                l += p0 + p1;
                const uint32_t pk = pack_bf16(p0, p1);
                pb[mt][0] = __shfl_sync(~0u, pk, 4 * t + (g & 1));
                pb[mt][1] = __shfl_sync(~0u, pk, 4 * (t + 4) + (g & 1));
            }
            l += __shfl_xor_sync(~0u, l, 4);
            l += __shfl_xor_sync(~0u, l, 8);
            l += __shfl_xor_sync(~0u, l, 16);
            float o[8][4];
#pragma unroll
            for (int i = 0; i < 8; i++) { o[i][0] = o[i][1] = o[i][2] = o[i][3] = 0.f; }
            mbar_wait(bar_v + warp * 8, ph ^ 1u);
#pragma unroll
            for (int kk = 0; kk < 4; kk++)
#pragma unroll
                for (int i = 0; i < 8; i++) {
                    uint32_t a[4];
                    ldsm4t(a, addr_kv(vb, kk * 16 + vkey, 2 * i + (mat & 1)));
                    mma16816(o[i], a, pb[kk][0], pb[kk][1]);
                }
            __syncwarp();
            if (lane == 0) mbar_arrive(bar_empty + warp * 8);
            const float inv = __fdividef(1.0f, l);
            const float inv1 = __shfl_down_sync(~0u, inv, 1);
            const int pair = tile / TPP, tt = tile % TPP;
            if (t == 0) {
                uint2* dst = g_po + ((size_t)pair * 8 * TPP + tt) * 8 + g;
#pragma unroll
                for (int qd = 0; qd < 4; qd++) {
                    st_relaxed2(dst + (size_t)qd * TPP * 8,
                                pack_tag(o[2 * qd][0] * inv, o[2 * qd][2] * inv, tag), pack_tag(o[2 * qd + 1][0] * inv, o[2 * qd + 1][2] * inv, tag));
                    st_relaxed2(dst + (size_t)(4 + qd) * TPP * 8,
                                pack_tag(o[2 * qd][1] * inv1, o[2 * qd][3] * inv1, tag), pack_tag(o[2 * qd + 1][1] * inv1, o[2 * qd + 1][3] * inv1, tag));
                }
            }
            {
                const uint32_t m_ = tagf(ms, tag), l_ = tagf(l, tag);
                const uint32_t m0 = __shfl_sync(~0u, m_, 0), l0 = __shfl_sync(~0u, l_, 0), m1 = __shfl_sync(~0u, m_, 1), l1 = __shfl_sync(~0u, l_, 1);
                if (lane < 2) st_relaxed4(g_ml + tile * 2 + lane, m0, l0, m1, l1);
            }
        }
        if (cta < NLATE) {
            {
                const uint32_t inv = tag ^ 1u;
                put_tile(fp_slot(cta, warp, g, t), inv, inv, inv, inv, true);
                if (warp < 2) st_relaxed4(g_h + (cta * 2 + warp) * 32 + lane, inv, inv, inv, inv);
            }
            const int stU = desc[4];
            ffn_unit<true>(sb, 0, sb + stU * STAGE, sb + ((stU + 1) % NST) * STAGE, bar_gdone, bar_lu, bar_ld, cta, warp, lane, tag);
        }
        if (cta < 128) {
            float* red = reinterpret_cast<float*>(sg + SM_RED);
            gather16(g_fp + cta * 36, red, tid, tag);
            bar_cons();
            if (tid < 36) {
                const float f = (red[tid] + red[36 + tid]) + (red[72 + tid] + red[108 + tid]);
                const float gate = bfr(silu_f(bfr(f)));
                mbar_wait(bar_ssum, 0);
                const float s = bfr((red[144 + tid] + red[180 + tid]) + (red[216 + tid] + red[252 + tid]));
                out[cta * 36 + tid] = __float2bfloat16_rn(xfin + bfr(s * gate));
            }
        }
    } else {
        const int cw = warp - NST - 1, ctid = tid - (NST + 1) * 32;
        const uint32_t tag = (epoch & 1u) ^ 1u;
        {
            const bool early = cta >= NPLAIN;
            asm volatile("bar.sync 0, %0;" :: "n"(NTHREADS), "r"(tag) : "memory");
            if (!early || cw == 3) {
                int tile = cta + cw * NPLAIN;
                if (early) {
                    mbar_wait(bar_first, 0);
                    tile = desc[3];
                } else {
                    mbar_wait(bar_wfree, 0);
                    __nanosleep(QDELAY);
                }
                const uint32_t* src = g_q + (tile / TPP) * 256 + lane * 4;
                uint4 v0, v1;
                Spin sp;
                while (true) {
                    v0 = ld_relaxed4(src); v1 = ld_relaxed4(src + 128);
                    if (!__any_sync(~0u, bad4(v0, tag) | bad4(v1, tag))) break;
                    __nanosleep(200);
                    sp.tick();
                }
                uint4* dst = reinterpret_cast<uint4*>(sg + cw * STAGE + 32768) + lane;
                dst[0] = v0; dst[32] = v1;
                __syncwarp();
                if (lane == 0) mbar_arrive(bar_q + cw * 8);
            }
            if (cw < 2 && cta < NLATE) {
                float acc[4];
                proj32<36>(acc, sb + SM_WBUF, bar_wg, sb + SM_XN, lane, cw, 0);
                put_frag(reinterpret_cast<float*>(sg + SM_GL), acc, cw, lane >> 2, lane & 3);
                __syncwarp();
                if (lane == 0) mbar_arrive(bar_gdone);
            }
        }
        if (cta < 128) {
            const int g = lane >> 2, t = lane & 3;
            const int hkv = cta >> 3, head = (cta >> 2) & 1, qd = cta & 3;
            uint32_t* sdst = g_sp + (hkv * NB + 2 * t) * DM + (cta & 7) * 72 + cw * 16 + g;
            const uint4* oxs = g_ox + (hkv * 8 * NB + g) * 8 + t;
            uint32_t ob[16][2];
            auto collect_o = [&](bool on) {
                uint4 v[16];
                Spin sp;
                while (true) {
                    uint32_t bad = 0;
                    if (on) {
#pragma unroll
                        for (int i = 0; i < 16; i++) v[i] = ld_relaxed4(oxs + (i >> 1) * (NB * 8) + (i & 1) * 4);
#pragma unroll
                        for (int i = 0; i < 16; i++) bad |= bad4(v[i], tag);
                    }
                    if (!__any_sync(~0u, bad)) break;
                    __nanosleep(30);
                    sp.tick();
                }
                if (on) {
#pragma unroll
                    for (int i = 0; i < 16; i++) { ob[i][0] = __byte_perm(v[i].x, v[i].y, 0x7632); ob[i][1] = __byte_perm(v[i].z, v[i].w, 0x7632); }
                }
            };
#pragma unroll 1
            for (int b = 0; b < NB; b++) {
                const int p = b * HKV + hkv;
                uint2 e;
                uint4 v[4];
                const uint2* rows = g_po + ((size_t)((p * 2 + head) * 4 + qd) * TPP + cw * 32 + g) * 8 + t * 2;
                {
                    const uint2* mlp = reinterpret_cast<const uint2*>(g_ml + (p * TPP + cw * 32 + lane) * 2) + head;
                    Spin sp;
                    const int plast = (p + 1) * TPP - NPLAIN * NST;
                                        const int target = min(plast + MARGIN, NDYN - TAILPOLL);
                    while (desc[9] < target) { __nanosleep(250); sp.tick(); }
                    if (b == NB - 1) collect_o(g < NB - 1);
                    while (true) {
                        e = ld_relaxed2(mlp);
                        const uint32_t miss = __ballot_sync(~0u, ((e.x ^ tag) | (e.y ^ tag)) & 1u);
                        if (!miss) break;
                        __nanosleep(miss == ~0u ? 300 : 20);
                        sp.tick();
                    }
                }
#pragma unroll
                for (int i = 0; i < 4; i++) v[i] = ld_relaxed4(rows + i * 64);
                const float m = untagf(e.x);
                float M = m;
#pragma unroll
                for (int o = 16; o; o >>= 1) M = fmaxf(M, __shfl_xor_sync(~0u, M, o));
                const float w = ex2(m - M) * untagf(e.y);
                float L = w;
#pragma unroll
                for (int o = 16; o; o >>= 1) L += __shfl_xor_sync(~0u, L, o);
                float wr[4];
#pragma unroll
                for (int i = 0; i < 4; i++) wr[i] = __shfl_sync(~0u, w, i * 8 + g);
                {
                    Spin sp;
                    while (__any_sync(~0u, bad4(v[0], tag) | bad4(v[1], tag) | bad4(v[2], tag) | bad4(v[3], tag))) {
#pragma unroll
                        for (int i = 0; i < 4; i++) v[i] = ld_relaxed4(rows + i * 64);
                        sp.tick();
                    }
                }
                float acc[8];
#pragma unroll
                for (int k = 0; k < 8; k++) acc[k] = 0.f;
#pragma unroll
                for (int i = 0; i < 4; i++) {
                    const uint32_t u[4] = {v[i].x, v[i].y, v[i].z, v[i].w};
#pragma unroll
                    for (int k = 0; k < 4; k++) {
                        acc[2 * k] = fmaf(wr[i], __uint_as_float((u[k] << 16) & 0xFFFE0000u), acc[2 * k]);
                        acc[2 * k + 1] = fmaf(wr[i], __uint_as_float(u[k] & 0xFFFF0000u), acc[2 * k + 1]);
                    }
                }
#pragma unroll
                for (int k = 0; k < 8; k++) {
                    acc[k] += __shfl_xor_sync(~0u, acc[k], 4);
                    acc[k] += __shfl_xor_sync(~0u, acc[k], 8);
                    acc[k] += __shfl_xor_sync(~0u, acc[k], 16);
                }
                float* part = reinterpret_cast<float*>(sg + SM_PART) + (b & 1) * 160;
                if (g == 0) {
#pragma unroll
                    for (int k = 0; k < 4; k++) *reinterpret_cast<float2*>(part + cw * 40 + k * 8 + 2 * t) = make_float2(acc[k], acc[k + 4]);
                    if (t == 0) *reinterpret_cast<float2*>(part + cw * 40 + 32) = make_float2(M, L);
                }
                bar_comb();
                if (ctid < 8) {
                    float2 ml4[4];
#pragma unroll
                    for (int i = 0; i < 4; i++) ml4[i] = *reinterpret_cast<const float2*>(part + i * 40 + 32);
                    const float MM = fmaxf(fmaxf(ml4[0].x, ml4[1].x), fmaxf(ml4[2].x, ml4[3].x));
                    float sw[4], LL = 0.f;
#pragma unroll
                    for (int i = 0; i < 4; i++) { sw[i] = ex2(ml4[i].x - MM); LL = fmaf(sw[i], ml4[i].y, LL); }
                    const float inv = 1.0f / LL;
                    uint32_t pk[2];
#pragma unroll
                    for (int j = 0; j < 2; j++) {
                        float o0 = 0.f, o1 = 0.f;
#pragma unroll
                        for (int i = 0; i < 4; i++) {
                            const float2 pv = *reinterpret_cast<const float2*>(part + i * 40 + g * 16 + j * 8 + 2 * t);
                            o0 = fmaf(sw[i], pv.x, o0); o1 = fmaf(sw[i], pv.y, o1);
                        }
                        pk[j] = pack_bf16(o0 * inv, o1 * inv);
                    }
                    uint4* dst = g_ox + (cta * NB + b) * 8 + ctid;
                    st_relaxed4(dst, (pk[0] << 16) | tag, (pk[0] & 0xFFFF0000u) | tag, (pk[1] << 16) | tag, (pk[1] & 0xFFFF0000u) | tag);
                    if (b == NB - 2) st_relaxed4(dst + 8, tag ^ 1u, tag ^ 1u, tag ^ 1u, tag ^ 1u);
                }
                if (b == NB - 2) {
                    const uint32_t inv = tag ^ 1u;
                    put_tile(sdst, inv, inv, inv, inv, true);
                    if (cw == 0) put_tile(sdst + 64, inv, inv, inv, inv, false);
                }
                __syncwarp();
            }
            {
                __nanosleep(ODELAY);
                const int m4 = lane >> 3;
                const uint32_t a0 = sb + SM_WBUF + ((m4 >> 1) * 8 + (lane & 7)) * 144 + (m4 & 1) * 16;
                uint32_t a[16][4], a2[4][4];
                auto load_a = [&]() {
#pragma unroll
                    for (int ks = 0; ks < 16; ks++) ldsm4t(a[ks], a0 + ks * (16 * 144) + cw * 32);
#pragma unroll
                    for (int i = 0; i < 4; i++) ldsm4t(a2[i], a0 + (cw * 4 + i) * (16 * 144) + 128);
                };
                bool have_a = false;
                const uint4* src = g_ox + ((hkv * 8 + (lane >> 3)) * NB + NB - 1) * 8 + (lane & 7);
                uint4 v0, v1;
                Spin sp;
                while (true) {
                    v0 = ld_relaxed4(src); v1 = ld_relaxed4(src + 4 * NB * 8);
                    if (!have_a && mbar_test(bar_wo, 0) && mbar_test(bar_wo + 8, 0) && mbar_test(bar_wo + 16, 0) && mbar_test(bar_wo + 24, 0)) { load_a(); have_a = true; }
                    if (!__any_sync(~0u, bad4(v0, tag) | bad4(v1, tag))) break;
                    sp.tick();
                }
                {
                    uint4* ox = reinterpret_cast<uint4*>(sg + SM_OB) + cw * 32;
                    ox[(lane & 3) * 8 + (lane >> 2)] = make_uint4(__byte_perm(v0.x, v0.y, 0x7632), __byte_perm(v0.z, v0.w, 0x7632),
                                                                  __byte_perm(v1.x, v1.y, 0x7632), __byte_perm(v1.z, v1.w, 0x7632));
                    __syncwarp();
                    if (g == NB - 1) {
#pragma unroll
                        for (int i = 0; i < 8; i++) { const uint4 w4 = ox[t * 8 + i]; ob[i][0] = w4.x; ob[i][1] = w4.y; ob[8 + i][0] = w4.z; ob[8 + i][1] = w4.w; }
                    }
                }
                float c0[4] = {0.f, 0.f, 0.f, 0.f}, c1[4] = {0.f, 0.f, 0.f, 0.f}, c2[4] = {0.f, 0.f, 0.f, 0.f};
                uint32_t b2[4][2];
#pragma unroll
                for (int i = 0; i < 4; i++) {
                    b2[i][0] = cw == 0 ? ob[i][0] : cw == 1 ? ob[4 + i][0] : cw == 2 ? ob[8 + i][0] : ob[12 + i][0];
                    b2[i][1] = cw == 0 ? ob[i][1] : cw == 1 ? ob[4 + i][1] : cw == 2 ? ob[8 + i][1] : ob[12 + i][1];
                }
                if (have_a) {
#pragma unroll
                    for (int i = 0; i < 4; i++) mma16816(c2, a2[i], b2[i][0], b2[i][1]);
#pragma unroll
                    for (int ks = 0; ks < 16; ks++) mma16816((ks & 1) ? c1 : c0, a[ks], ob[ks][0], ob[ks][1]);
                } else {
#pragma unroll
                    for (int pc = 0; pc < 4; pc++) {
                        mbar_wait(bar_wo + pc * 8, 0);
#pragma unroll
                        for (int i = 0; i < 4; i++) ldsm4t(a[i], a0 + (pc * 4 + i) * (16 * 144) + cw * 32);
                        if (pc == cw) {
#pragma unroll
                            for (int i = 0; i < 4; i++) ldsm4t(a2[i], a0 + (pc * 4 + i) * (16 * 144) + 128);
#pragma unroll
                            for (int i = 0; i < 4; i++) mma16816(c2, a2[i], b2[i][0], b2[i][1]);
                        }
#pragma unroll
                        for (int i = 0; i < 4; i++) mma16816((i & 1) ? c1 : c0, a[i], ob[pc * 4 + i][0], ob[pc * 4 + i][1]);
                    }
                }
                float2* x4 = reinterpret_cast<float2*>(sg + SM_PART);
                x4[cw * 32 + lane] = make_float2(c2[0], c2[1]);
                put_tile(sdst, tagf(c0[0] + c1[0], tag), tagf(c0[1] + c1[1], tag), tagf(c0[2] + c1[2], tag), tagf(c0[3] + c1[3], tag), true);
                bar_comb();
                if (cw == 0) {
                    const float2 p0 = x4[lane], p1 = x4[32 + lane], p2 = x4[64 + lane], p3 = x4[96 + lane];
                    put_tile(sdst + 64, tagf((p0.x + p1.x) + (p2.x + p3.x), tag), tagf((p0.y + p1.y) + (p2.y + p3.y), tag), 0, 0, false);
                }
            }
            gather16(g_sp + cta * 36, reinterpret_cast<float*>(sg + SM_RED) + 144, ctid, tag);
            __syncwarp();
            if (lane == 0) mbar_arrive(bar_ssum);
        }
    }
}

__device__ float f_q[NB * 4096], f_h[NB * FF], f_o[NB * 4096];

__global__ void fb_proj(const __nv_bfloat16* x, const __nv_bfloat16* wq, const __nv_bfloat16* wg, const __nv_bfloat16* wu) {
    __shared__ float xn[DM];
    const int b = blockIdx.y, n = blockIdx.x * blockDim.x + threadIdx.x;
    float s = 0.f, q = 0.f;
    for (int i = 0; i < DM; i++) s += __bfloat162float(x[b * DM + i]);
    const float mean = s / DM;
    for (int i = 0; i < DM; i++) { const float d = __bfloat162float(x[b * DM + i]) - mean; q += d * d; }
    const float den = bfr(sqrtf(bfr(bfr(q / DM) + 1e-5f)));
    for (int i = threadIdx.x; i < DM; i += blockDim.x) xn[i] = bfr(bfr(__bfloat162float(x[b * DM + i]) - bfr(mean)) / den);
    __syncthreads();
    if (n < 4096) {
        float a = 0.f;
        for (int k = 0; k < DM; k++) a += xn[k] * __bfloat162float(wq[(size_t)k * 4096 + n]);
        f_q[b * 4096 + n] = bfr(a);
    }
    if (n < FF) {
        float g = 0.f, u = 0.f;
        for (int k = 0; k < DM; k++) { g += xn[k] * __bfloat162float(wg[(size_t)k * FF + n]); u += xn[k] * __bfloat162float(wu[(size_t)k * FF + n]); }
        f_h[b * FF + n] = bfr(bfr(silu_f(bfr(g))) * bfr(u));
    }
}
__global__ void fb_attn(const __nv_bfloat16* K, const __nv_bfloat16* V) {
    __shared__ float sc[SK], red[128];
    const int t = threadIdx.x, b = blockIdx.x >> 5, h = blockIdx.x & 31;
    const __nv_bfloat16* k = K + (size_t)(b * HKV + (h >> 1)) * SK * 128;
    const __nv_bfloat16* v = V + (size_t)(b * HKV + (h >> 1)) * SK * 128;
    const float* q = f_q + b * 4096 + h * 128;
    float m = -INFINITY, l = 0.f, o = 0.f;
    for (int j = t; j < SK; j += 128) {
        float s = 0.f;
        for (int d = 0; d < 128; d++) s += q[d] * __bfloat162float(k[(size_t)j * 128 + d]);
        sc[j] = s * 0.08838834764831845f; m = fmaxf(m, sc[j]);
    }
    red[t] = m; __syncthreads();
    for (int i = 0; i < 128; i++) m = fmaxf(m, red[i]);
    __syncthreads();
    for (int j = t; j < SK; j += 128) { sc[j] = __expf(sc[j] - m); l += sc[j]; }
    red[t] = l; __syncthreads();
    l = 0.f;
    for (int i = 0; i < 128; i++) l += red[i];
    for (int j = 0; j < SK; j++) o += sc[j] * __bfloat162float(v[(size_t)j * 128 + t]);
    f_o[b * 4096 + h * 128 + t] = bfr(o / l);
}
__global__ void fb_out(const __nv_bfloat16* x, const __nv_bfloat16* wo, const __nv_bfloat16* wd, __nv_bfloat16* out) {
    const int b = blockIdx.y, n = blockIdx.x * blockDim.x + threadIdx.x;
    float s = 0.f, f = 0.f;
    for (int k = 0; k < 4096; k++) s += f_o[b * 4096 + k] * __bfloat162float(wo[(size_t)k * DM + n]);
    for (int k = 0; k < FF; k++) f += f_h[b * FF + k] * __bfloat162float(wd[(size_t)k * DM + n]);
    out[b * DM + n] = __float2bfloat16_rn(__bfloat162float(x[b * DM + n]) + bfr(bfr(s) * bfr(silu_f(bfr(f)))));
}

typedef CUresult (*EncodeFn)(CUtensorMap*, CUtensorMapDataType, cuuint32_t, void*, const cuuint64_t*, const cuuint64_t*,
                             const cuuint32_t*, const cuuint32_t*, CUtensorMapInterleave, CUtensorMapSwizzle,
                             CUtensorMapL2promotion, CUtensorMapFloatOOBfill);

void make_map(EncodeFn enc, CUtensorMap* m, const void* p, int rank, const cuuint64_t* dims, const cuuint64_t* strides,
              const cuuint32_t* box, CUtensorMapSwizzle sw, CUtensorMapL2promotion promo) {
    cuuint32_t es[3] = {1, 1, 1};
    enc(m, CU_TENSOR_MAP_DATA_TYPE_BFLOAT16, rank, const_cast<void*>(p), dims, strides, box, es,
        CU_TENSOR_MAP_INTERLEAVE_NONE, sw, promo, CU_TENSOR_MAP_FLOAT_OOB_FILL_NONE);
}

}

extern "C" void kernel_launch(void* const* d_in, const int* in_sizes, int n_in, void* d_out, int out_size) {
    (void)in_sizes; (void)n_in; (void)out_size;
    static EncodeFn enc = nullptr;
    static int mode = 0;
    if (!mode) {
        void* fn = nullptr;
        cudaDriverEntryPointQueryResult qr;
        cudaGetDriverEntryPoint("cuTensorMapEncodeTiled", &fn, cudaEnableDefault, &qr);
        enc = (EncodeFn)fn;
        int dev = 0, sms = 0, occ = 0;
        cudaGetDevice(&dev);
        cudaDeviceGetAttribute(&sms, cudaDevAttrMultiProcessorCount, dev);
        cudaFuncSetAttribute(fused_decode_kernel, cudaFuncAttributeMaxDynamicSharedMemorySize, SMEM_BYTES);
        cudaOccupancyMaxActiveBlocksPerMultiprocessor(&occ, fused_decode_kernel, NTHREADS, SMEM_BYTES);
        mode = (enc && occ * sms >= NCTA) ? 1 : 2;
    }
    typedef const __nv_bfloat16* P;
    if (mode == 2) {
        fb_proj<<<dim3(FF / 128, NB), 128>>>((P)d_in[0], (P)d_in[3], (P)d_in[6], (P)d_in[7]);
        fb_attn<<<NB * 32, 128>>>((P)d_in[1], (P)d_in[2]);
        fb_out<<<dim3(DM / 64, NB), 64>>>((P)d_in[0], (P)d_in[4], (P)d_in[8], (__nv_bfloat16*)d_out);
        return;
    }
    Maps maps;
    const cuuint64_t kvrows = (cuuint64_t)NPAIR * SK;
    for (int i = 0; i < 2; i++) {
        cuuint64_t dims[3] = {64, kvrows, 2}, strides[2] = {256, 128};
        cuuint32_t box[3] = {64, TILE, 2};
        make_map(enc, i ? &maps.v : &maps.k, d_in[1 + i], 3, dims, strides, box, CU_TENSOR_MAP_SWIZZLE_128B, CU_TENSOR_MAP_L2_PROMOTION_L2_256B);
    }
    {
        cuuint32_t box[2] = {32, 192};
        cuuint64_t dq[2] = {4096, DM}, sq[1] = {4096 * 2};
        make_map(enc, &maps.wq, d_in[3], 2, dq, sq, box, CU_TENSOR_MAP_SWIZZLE_64B, CU_TENSOR_MAP_L2_PROMOTION_L2_128B);
        cuuint64_t df[2] = {FF, DM}, sf[1] = {FF * 2};
        make_map(enc, &maps.wg, d_in[6], 2, df, sf, box, CU_TENSOR_MAP_SWIZZLE_64B, CU_TENSOR_MAP_L2_PROMOTION_L2_128B);
        make_map(enc, &maps.wu, d_in[7], 2, df, sf, box, CU_TENSOR_MAP_SWIZZLE_64B, CU_TENSOR_MAP_L2_PROMOTION_L2_128B);
    }
    {
        cuuint32_t boxo[2] = {72, 64};
        cuuint64_t d_o[2] = {DM, 4096}, s_o[1] = {DM * 2};
        make_map(enc, &maps.wo, d_in[4], 2, d_o, s_o, boxo, CU_TENSOR_MAP_SWIZZLE_NONE, CU_TENSOR_MAP_L2_PROMOTION_L2_128B);
        cuuint32_t boxd[2] = {64, 96};
        cuuint64_t d_d[2] = {DM, FF}, s_d[1] = {DM * 2};
        make_map(enc, &maps.wd, d_in[8], 2, d_d, s_d, boxd, CU_TENSOR_MAP_SWIZZLE_128B, CU_TENSOR_MAP_L2_PROMOTION_L2_128B);
    }
    fused_decode_kernel<<<NCTA, NTHREADS, SMEM_BYTES>>>(maps, (const __nv_bfloat16*)d_in[0], (__nv_bfloat16*)d_out);
}
```

```cpp
#include <cuda_runtime.h>
#include <cuda_bf16.h>
#include <cuda.h>
#include <math.h>
#include <stdint.h>

namespace {

constexpr int NB = 8, DM = 576, HKV = 16, SK = 8192, FF = 4608;
constexpr int NPAIR = NB * HKV;
constexpr int TILE = 64;
constexpr int TPP = SK / TILE;
constexpr int NKV = NPAIR * TPP;
constexpr int NCTA = 132;
constexpr int NST = 4;
constexpr int STAGE = 36864;
constexpr int NUNIT = FF / 32;
constexpr int GRP = 9;
constexpr int NGRP = NUNIT / GRP;
constexpr int NLATE = (NCTA / GRP) * GRP;
constexpr int NEARLY = NUNIT - NLATE;
constexpr int NPLAIN = NCTA - NEARLY;
constexpr int NDYN = NKV - NPLAIN * NST;
constexpr int XP = 584;
constexpr int NTHREADS = 288;

constexpr int INFLIGHT = 3;
constexpr int SPIECES = 4;
constexpr int EPIECES = 4;
constexpr int LATECLAIM = 400;
constexpr int PEEK = 200;
constexpr int MARGIN = 600;
constexpr int TAILPOLL = 900;
constexpr int QDELAY = 800, HDELAY = 700, ODELAY = 400;

constexpr int SM_WBUF = NST * STAGE;
constexpr int SM_XN = SM_WBUF + STAGE;
constexpr int SM_GU = SM_XN + NB * XP * 2;
constexpr int SM_GL = SM_GU + 2 * 8 * 36 * 4;
constexpr int SM_HB = SM_GL + 8 * 36 * 4;
constexpr int SM_RED = SM_HB + 2 * GRP * 32 * 8;
constexpr int SM_PART = SM_RED + 2 * 4 * 36 * 4;
constexpr int SM_OB = SM_PART + 2 * 4 * 40 * 4;
constexpr int SM_BAR = SM_OB + 4 * 512;
constexpr int NBAR = 4 * NST + 29;
constexpr int SM_DESC = SM_BAR + NBAR * 8;
constexpr int SM_TOTAL = SM_DESC + 64;
constexpr int SMEM_BYTES = SM_TOTAL + 1024;

struct Maps { CUtensorMap k, v, wq, wg, wu, wo, wd; };

__device__ __align__(128) unsigned g_queue[32];
__device__ __align__(128) unsigned g_state[32];
__device__ __align__(128) uint32_t g_q[NPAIR * 256];
__device__ __align__(128) uint4 g_ml[NKV * 2];
__device__ __align__(128) uint2 g_po[NPAIR * 2 * 4 * TPP * 8];
__device__ __align__(128) uint4 g_ox[128 * NB * 8];
__device__ __align__(128) uint32_t g_sp[HKV * NB * DM];
__device__ __align__(128) uint32_t g_fp[NGRP * NB * DM];
__device__ __align__(128) uint4 g_h[NUNIT * 2 * 32];

__device__ __forceinline__ uint32_t s2u(const void* p) { return (uint32_t)__cvta_generic_to_shared(p); }
__device__ __forceinline__ void mbar_init(uint32_t b, int c) { asm volatile("mbarrier.init.shared::cta.b64 [%0], %1;" :: "r"(b), "r"(c)); }
__device__ __forceinline__ void mbar_expect(uint32_t b, uint32_t bytes) { asm volatile("mbarrier.arrive.expect_tx.shared::cta.b64 _, [%0], %1;" :: "r"(b), "r"(bytes) : "memory"); }
__device__ __forceinline__ void mbar_arrive(uint32_t b) { asm volatile("mbarrier.arrive.shared::cta.b64 _, [%0];" :: "r"(b) : "memory"); }
__device__ __forceinline__ bool mbar_try(uint32_t b, uint32_t ph) {
    uint32_t ok;
    asm volatile("{\n.reg .pred p;\nmbarrier.try_wait.parity.shared::cta.b64 p, [%1], %2;\nselp.u32 %0, 1, 0, p;\n}" : "=r"(ok) : "r"(b), "r"(ph) : "memory");
    return ok != 0;
}
__device__ __forceinline__ bool mbar_test(uint32_t b, uint32_t ph) {
    uint32_t ok;
    asm volatile("{\n.reg .pred p;\nmbarrier.test_wait.parity.shared::cta.b64 p, [%1], %2;\nselp.u32 %0, 1, 0, p;\n}" : "=r"(ok) : "r"(b), "r"(ph) : "memory");
    return ok != 0;
}
constexpr long long SPIN_LIMIT = 4000000000LL;
__device__ __forceinline__ void mbar_wait(uint32_t b, uint32_t ph) {
    if (mbar_try(b, ph)) return;
    long long t0 = clock64();
    while (!mbar_try(b, ph)) { if (clock64() - t0 > SPIN_LIMIT) __trap(); }
}
struct Spin {
    long long t0 = 0;
    __device__ __forceinline__ void tick() { long long t = clock64(); if (t0 == 0) t0 = t; else if (t - t0 > SPIN_LIMIT) __trap(); }
};
__device__ __forceinline__ void bulk_g2s(uint32_t dst, const void* src, uint32_t bytes, uint32_t bar) {
    asm volatile("cp.async.bulk.shared::cluster.global.mbarrier::complete_tx::bytes [%0], [%1], %2, [%3];" :: "r"(dst), "l"(src), "r"(bytes), "r"(bar) : "memory");
}
__device__ __forceinline__ void tma2d(uint32_t dst, const CUtensorMap* m, int c0, int c1, uint32_t bar) {
    asm volatile("cp.async.bulk.tensor.2d.shared::cluster.global.mbarrier::complete_tx::bytes [%0], [%1, {%3, %4}], [%2];" :: "r"(dst), "l"(m), "r"(bar), "r"(c0), "r"(c1) : "memory");
}
__device__ __forceinline__ void tma3d(uint32_t dst, const CUtensorMap* m, int c0, int c1, int c2, uint32_t bar, uint64_t pol) {
    asm volatile("cp.async.bulk.tensor.3d.shared::cluster.global.mbarrier::complete_tx::bytes.L2::cache_hint [%0], [%1, {%3, %4, %5}], [%2], %6;" :: "r"(dst), "l"(m), "r"(bar), "r"(c0), "r"(c1), "r"(c2), "l"(pol) : "memory");
}
__device__ __forceinline__ void ldsm4(uint32_t (&r)[4], uint32_t a) {
    asm volatile("ldmatrix.sync.aligned.m8n8.x4.shared.b16 {%0,%1,%2,%3}, [%4];" : "=r"(r[0]), "=r"(r[1]), "=r"(r[2]), "=r"(r[3]) : "r"(a));
}
__device__ __forceinline__ void ldsm4t(uint32_t (&r)[4], uint32_t a) {
    asm volatile("ldmatrix.sync.aligned.m8n8.x4.trans.shared.b16 {%0,%1,%2,%3}, [%4];" : "=r"(r[0]), "=r"(r[1]), "=r"(r[2]), "=r"(r[3]) : "r"(a));
}
__device__ __forceinline__ void mma16816(float (&c)[4], const uint32_t (&a)[4], uint32_t b0, uint32_t b1) {
    asm("mma.sync.aligned.m16n8k16.row.col.f32.bf16.bf16.f32 {%0,%1,%2,%3}, {%4,%5,%6,%7}, {%8,%9}, {%0,%1,%2,%3};"
                 : "+f"(c[0]), "+f"(c[1]), "+f"(c[2]), "+f"(c[3]) : "r"(a[0]), "r"(a[1]), "r"(a[2]), "r"(a[3]), "r"(b0), "r"(b1));
}
__device__ __forceinline__ uint4 ld_relaxed4(const void* p) {
    uint4 v; asm volatile("ld.relaxed.gpu.global.v4.u32 {%0,%1,%2,%3}, [%4];" : "=r"(v.x), "=r"(v.y), "=r"(v.z), "=r"(v.w) : "l"(p) : "memory"); return v;
}
__device__ __forceinline__ uint2 ld_relaxed2(const void* p) {
    uint2 v; asm volatile("ld.relaxed.gpu.global.v2.u32 {%0,%1}, [%2];" : "=r"(v.x), "=r"(v.y) : "l"(p) : "memory"); return v;
}
__device__ __forceinline__ uint32_t ld_relaxed1(const void* p) {
    uint32_t v; asm volatile("ld.relaxed.gpu.global.u32 %0, [%1];" : "=r"(v) : "l"(p) : "memory"); return v;
}
__device__ __forceinline__ void st_relaxed4(void* p, uint32_t a, uint32_t b, uint32_t c, uint32_t d) {
    asm volatile("st.relaxed.gpu.global.v4.u32 [%0], {%1,%2,%3,%4};" :: "l"(p), "r"(a), "r"(b), "r"(c), "r"(d) : "memory");
}
__device__ __forceinline__ void st_relaxed1(void* p, uint32_t a) {
    asm volatile("st.relaxed.gpu.global.u32 [%0], %1;" :: "l"(p), "r"(a) : "memory");
}
__device__ __forceinline__ void st_relaxed2(void* p, uint32_t a, uint32_t b) {
    asm volatile("st.relaxed.gpu.global.v2.u32 [%0], {%1,%2};" :: "l"(p), "r"(a), "r"(b) : "memory");
}
__device__ __forceinline__ uint4 lds128(uint32_t a) { uint4 v; asm volatile("ld.shared.v4.u32 {%0,%1,%2,%3}, [%4];" : "=r"(v.x), "=r"(v.y), "=r"(v.z), "=r"(v.w) : "r"(a) : "memory"); return v; }
__device__ __forceinline__ void bar_cons() { asm volatile("bar.sync 1, 128;" ::: "memory"); }
__device__ __forceinline__ void bar_comb() { asm volatile("bar.sync 2, 128;" ::: "memory"); }
__device__ __forceinline__ float bfr(float v) { return __bfloat162float(__float2bfloat16_rn(v)); }
__device__ __forceinline__ uint32_t pack_bf16(float lo, float hi) {
    uint32_t r; asm("cvt.rn.bf16x2.f32 %0, %1, %2;" : "=r"(r) : "f"(hi), "f"(lo)); return r;
}
__device__ __forceinline__ float ex2(float x) { float y; asm("ex2.approx.ftz.f32 %0, %1;" : "=f"(y) : "f"(x)); return y; }
__device__ __forceinline__ float silu_f(float v) { return __fdividef(v, 1.0f + __expf(-v)); }
__device__ __forceinline__ uint32_t tagf(float v, uint32_t tag) { return (__float_as_uint(v) & ~1u) | tag; }
__device__ __forceinline__ float untagf(uint32_t w) { return __uint_as_float(w & ~1u); }
__device__ __forceinline__ uint32_t bad4(const uint4& v, uint32_t tag) { return ((v.x ^ tag) | (v.y ^ tag) | (v.z ^ tag) | (v.w ^ tag)) & 1u; }
__device__ __forceinline__ uint32_t pack_tag(float lo, float hi, uint32_t tag) {
    uint32_t l = ((__float_as_uint(lo) + 0x10000u) >> 16) & 0xFFFEu;
    uint32_t h = pack_bf16(0.f, hi) & 0xFFFF0000u;
    return h | l | tag;
}

__device__ __forceinline__ int dyn_tile(int n) { return n + NPLAIN * NST; }

__device__ __forceinline__ uint32_t addr_w32(uint32_t base, int lane, int mt, int ks) {
    int mat = lane >> 3, row = ks * 16 + (mat >> 1) * 8 + (lane & 7), c = mt * 2 + (mat & 1);
    return base + row * 64 + ((c ^ ((row >> 1) & 3)) << 4);
}
__device__ __forceinline__ uint32_t addr_kv(uint32_t base, int key, int chunk) {
    return base + (chunk >> 3) * 8192 + key * 128 + (((chunk & 7) ^ (key & 7)) << 4);
}

template <int NKS>
__device__ __forceinline__ void proj32(float (&acc)[4], uint32_t wbase, uint32_t bar, uint32_t xn, int lane, int mt, int ks0) {
    uint32_t xb[NKS / 2][4];
    const uint32_t xa = xn + ((lane & 7) * XP + (lane >> 3) * 8 + ks0 * 16) * 2;
#pragma unroll
    for (int i = 0; i < NKS / 2; i++) ldsm4(xb[i], xa + i * 64);
    float a4[4][4];
#pragma unroll
    for (int i = 0; i < 4; i++) { a4[i][0] = a4[i][1] = a4[i][2] = a4[i][3] = 0.f; }
    const uint32_t wa = addr_w32(wbase, lane, mt, ks0);
    if (ks0 < 12) mbar_wait(bar, 0);
    mbar_wait(bar + 8, 0);
    if (ks0 + NKS > 24) mbar_wait(bar + 16, 0);
#pragma unroll
    for (int i = 0; i < NKS; i++) {
        uint32_t a[4];
        ldsm4t(a, wa + i * 1024);
        mma16816(a4[i & 3], a, xb[i >> 1][(i & 1) * 2], xb[i >> 1][(i & 1) * 2 + 1]);
    }
#pragma unroll
    for (int i = 0; i < 4; i++) acc[i] = (a4[0][i] + a4[1][i]) + (a4[2][i] + a4[3][i]);
}

__device__ __forceinline__ void put_frag(float* dst, const float (&acc)[4], int mt, int g, int t) {
    dst[(2 * t) * 36 + mt * 16 + g] = acc[0];
    dst[(2 * t + 1) * 36 + mt * 16 + g] = acc[1];
    dst[(2 * t) * 36 + mt * 16 + g + 8] = acc[2];
    dst[(2 * t + 1) * 36 + mt * 16 + g + 8] = acc[3];
}
__device__ __forceinline__ void put_tile(uint32_t* dst, uint32_t w0, uint32_t w1, uint32_t w2, uint32_t w3, bool upper) {
    st_relaxed1(dst, w0); st_relaxed1(dst + DM, w1);
    if (upper) { st_relaxed1(dst + 8, w2); st_relaxed1(dst + DM + 8, w3); }
}
__device__ __forceinline__ uint32_t* fp_slot(int unit, int warp, int g, int t) {
    return g_fp + ((unit / GRP) * NB + 2 * t) * DM + (unit % GRP) * 64 + warp * 16 + g;
}

template <bool LATE>
__device__ __forceinline__ void ffn_unit(uint32_t sb, uint32_t bufG, uint32_t bufU, uint32_t bufD, uint32_t barG, uint32_t barU,
                                         uint32_t barD, int unit, int warp, int lane, uint32_t tag) {
    const int g = lane >> 2, t = lane & 3;
    const int hf = warp >> 1, mt = warp & 1;
    float* gu = reinterpret_cast<float*>(__cvta_shared_to_generic(sb + SM_GU));
    float acc[4];
    if (LATE) { mbar_wait(barG, 0); proj32<18>(acc, bufU, barU, sb + SM_XN, lane, mt, hf * 18); }
    else proj32<36>(acc, hf ? bufU : bufG, hf ? barU : barG, sb + SM_XN, lane, mt, 0);
    put_frag(gu + hf * 288, acc, mt, g, t);
    bar_cons();
    if (warp < 2) {
        uint32_t hw[2];
#pragma unroll
        for (int j = 0; j < 2; j++) {
            const int f = g * 36 + warp * 16 + j * 8 + 2 * t;
            const float2 p0 = *reinterpret_cast<const float2*>(gu + f), p1 = *reinterpret_cast<const float2*>(gu + 288 + f);
            float2 gg = p0, uu = p1;
            if (LATE) { gg = *reinterpret_cast<const float2*>(gu + 576 + f); uu = make_float2(p0.x + p1.x, p0.y + p1.y); }
            hw[j] = pack_bf16(bfr(silu_f(bfr(gg.x))) * bfr(uu.x), bfr(silu_f(bfr(gg.y))) * bfr(uu.y));
        }
        st_relaxed4(g_h + (unit * 2 + warp) * 32 + lane, (hw[0] << 16) | tag, (hw[0] & 0xFFFF0000u) | tag, (hw[1] << 16) | tag, (hw[1] & 0xFFFF0000u) | tag);
    }
    {
        const uint4* src = g_h + (unit / GRP) * (2 * GRP * 32) + warp * 32 + lane;
        uint4 v[5];
        uint32_t pend = warp < 2 ? 0x1Fu : 0xFu;
        Spin sp;
        if (LATE) __nanosleep(HDELAY);
        while (true) {
#pragma unroll
            for (int i = 0; i < 5; i++)
                if (pend >> i & 1) v[i] = ld_relaxed4(src + i * 128);
#pragma unroll
            for (int i = 0; i < 5; i++)
                if ((pend >> i & 1) && !__any_sync(~0u, bad4(v[i], tag))) {
                    pend &= ~(1u << i);
                    asm volatile("st.shared.v2.u32 [%0], {%1, %2};" :: "r"(sb + SM_HB + ((i * 4 + warp) * 32 + lane) * 8),
                                 "r"(__byte_perm(v[i].x, v[i].y, 0x7632)), "r"(__byte_perm(v[i].z, v[i].w, 0x7632)) : "memory");
                }
            if (!pend) break;
            __nanosleep(30);
            sp.tick();
        }
    }
    mbar_wait(barD, 0); mbar_wait(barD + 8, 0); mbar_wait(barD + 16, 0);
    uint32_t a[2 * GRP][4];
    {
        const int m4 = lane >> 3, row = (m4 >> 1) * 8 + (lane & 7), c = warp * 2 + (m4 & 1);
        const uint32_t a0 = bufD + row * 128 + ((c ^ (lane & 7)) << 4);
#pragma unroll
        for (int ks = 0; ks < 2 * GRP; ks++) ldsm4t(a[ks], a0 + ks * 2048);
    }
    bar_cons();
    float c0[4] = {0.f, 0.f, 0.f, 0.f}, c1[4] = {0.f, 0.f, 0.f, 0.f}, c2[4] = {0.f, 0.f, 0.f, 0.f};
#pragma unroll
    for (int ks = 0; ks < 2 * GRP; ks++) {
        uint32_t h0, h1;
        asm volatile("ld.shared.v2.u32 {%0, %1}, [%2];" : "=r"(h0), "=r"(h1) : "r"(sb + SM_HB + (ks * 32 + lane) * 8) : "memory");
        mma16816(ks % 3 == 0 ? c0 : ks % 3 == 1 ? c1 : c2, a[ks], h0, h1);
    }
    put_tile(fp_slot(unit, warp, g, t), tagf(c0[0] + c1[0] + c2[0], tag), tagf(c0[1] + c1[1] + c2[1], tag),
             tagf(c0[2] + c1[2] + c2[2], tag), tagf(c0[3] + c1[3] + c2[3], tag), true);
}

__device__ __forceinline__ void gather16(const uint32_t* base, float* red, int tid, uint32_t tag) {
    const int f = tid & 7;
    const uint32_t* src = base + (tid >> 3) * (NB * DM) + f * 4;
    uint4 v0, v1 = make_uint4(tag, tag, tag, tag);
    Spin sp;
    while (true) {
        v0 = ld_relaxed4(src);
        if (f == 0) v1 = ld_relaxed4(src + 32);
        if (!__any_sync(~0u, bad4(v0, tag) | bad4(v1, tag))) break;
        __nanosleep(30);
        sp.tick();
    }
    float a[8] = {untagf(v0.x), untagf(v0.y), untagf(v0.z), untagf(v0.w), untagf(v1.x), untagf(v1.y), untagf(v1.z), untagf(v1.w)};
#pragma unroll
    for (int i = 0; i < 8; i++) { a[i] += __shfl_xor_sync(~0u, a[i], 8); a[i] += __shfl_xor_sync(~0u, a[i], 16); }
    if ((tid & 31) < 8) {
        float* r = red + (tid >> 5) * 36;
        *reinterpret_cast<float4*>(r + f * 4) = make_float4(a[0], a[1], a[2], a[3]);
        if (f == 0) *reinterpret_cast<float4*>(r + 32) = make_float4(a[4], a[5], a[6], a[7]);
    }
}

__global__ void __launch_bounds__(NTHREADS, 1)
fused_decode_kernel(const __grid_constant__ Maps maps, const __nv_bfloat16* __restrict__ x, __nv_bfloat16* __restrict__ out) {
    extern __shared__ uint8_t smem_raw[];
    const uint32_t sb = (s2u(smem_raw) + 1023u) & ~1023u;
    uint8_t* sg = smem_raw + (sb - s2u(smem_raw));
    const int tid = threadIdx.x, warp = tid >> 5, lane = tid & 31, cta = blockIdx.x;
    const uint32_t bar_full = sb + SM_BAR, bar_empty = bar_full + NST * 8;
    const uint32_t bar_q = bar_empty + NST * 8, bar_v = bar_q + NST * 8;
    const uint32_t bar_wq = bar_v + NST * 8, bar_wg = bar_wq + 24;
    const uint32_t bar_e = bar_wg + 24;
    const uint32_t bar_lu = bar_e + 72, bar_ld = bar_lu + 24, bar_wo = bar_ld + 24;
    const uint32_t bar_ssum = bar_wo + 32, bar_first = bar_ssum + 8, bar_wfree = bar_first + 8, bar_gdone = bar_wfree + 8;
    volatile int* desc = reinterpret_cast<volatile int*>(sg + SM_DESC);

    uint32_t xr[2][9];
    if (warp < NST) {
#pragma unroll
        for (int r = 0; r < 2; r++)
#pragma unroll
            for (int i = 0; i < 9; i++)
                asm volatile("ld.global.nc.u32 %0, [%1];" : "=r"(xr[r][i]) : "l"(reinterpret_cast<const uint32_t*>(x + (warp * 2 + r) * DM) + i * 32 + lane));
    }
    if (tid >= 160 && tid < 167) asm volatile("prefetch.tensormap [%0];" :: "l"(reinterpret_cast<const CUtensorMap*>(&maps) + (tid - 160)) : "memory");
    uint32_t epoch = 0;
    if (warp != NST) epoch = ld_relaxed1(&g_state[1]);
    if (tid == NST * 32) {
        mbar_init(bar_wq, 1); mbar_init(bar_wq + 8, 1); mbar_init(bar_wq + 16, 1); mbar_init(bar_full, 1); mbar_init(bar_e, 1);
        asm volatile("fence.mbarrier_init.release.cluster;" ::: "memory");
        if (cta < 128) {
#pragma unroll
            for (int i = 0; i < 3; i++) { mbar_expect(bar_wq + i * 8, 12288); tma2d(sb + SM_WBUF + i * 12288, &maps.wq, cta * 32, i * 192, bar_wq + i * 8); }
        }
        if (cta >= NPLAIN) { mbar_expect(bar_e, 12288); tma2d(sb, &maps.wg, (NLATE + cta - NPLAIN) * 32, 0, bar_e); }
        else {
            uint64_t pol; asm volatile("createpolicy.fractional.L2::evict_first.b64 %0, 1.0;" : "=l"(pol));
            mbar_expect(bar_full, 16384);
            tma3d(sb, &maps.k, 0, cta * TILE, 0, bar_full, pol);
        }
    }

    if (warp == NST) {
        uint64_t pol; asm volatile("createpolicy.fractional.L2::evict_first.b64 %0, 1.0;" : "=l"(pol));
        constexpr int FN = 4, F0 = FN - INFLIGHT;
        uint32_t fifo[FN];
#pragma unroll
        for (int i = 0; i < FN; i++) fifo[i] = 0;
        auto gate = [&](int n) { for (int i = F0; i < F0 + n; i++) if (fifo[i]) mbar_wait(fifo[i] & ~1u, fifo[i] & 1u); };
        auto push = [&](uint32_t bar, uint32_t par) {
#pragma unroll
            for (int i = 0; i + 1 < FN; i++) fifo[i] = fifo[i + 1];
            fifo[FN - 1] = bar | par;
        };
        auto issue_half = [&](const CUtensorMap* m, int tile, uint32_t dst, uint32_t bar, uint32_t par) {
            mbar_expect(bar, 16384);
            tma3d(dst, m, 0, tile * TILE, 0, bar, pol);
            push(bar, par);
        };
        auto issue_k = [&](int tile, int st, uint32_t par) { desc[st] = tile; issue_half(&maps.k, tile, sb + st * STAGE, bar_full + st * 8, par); };
        auto issue_v = [&](int tile, int st, uint32_t par) { issue_half(&maps.v, tile, sb + st * STAGE + 16384, bar_v + st * 8, par); };
        auto piece = [&](const CUtensorMap* m, int c0, int c1, uint32_t dst, uint32_t bar, uint32_t bytes) {
            mbar_expect(bar, bytes);
            tma2d(dst, m, c0, c1, bar);
            push(bar, 0);
        };
        auto col_piece = [&](const CUtensorMap* m, int unit, int i, uint32_t buf, uint32_t bar) { piece(m, unit * 32, i * 192, buf + i * 12288, bar + i * 8, 12288); };
        auto down_piece = [&](int unit, int i, uint32_t buf, uint32_t bar) {
            piece(&maps.wd, (unit % GRP) * 64, (unit / GRP) * (GRP * 32) + i * 96, buf + i * 12288, bar + i * 8, 12288);
        };
        auto gate4 = [&]() { const uint32_t f = fifo[FN - SPIECES]; if (f) mbar_wait(f & ~1u, f & 1u); };
        const bool early = cta >= NPLAIN;
        const int eunit = NLATE + cta - NPLAIN;
        int next = 0;
        auto claim = [&]() { return (int)atomicAdd(&g_queue[0], 1u); };
        if (lane == 0) {
            if (cta < 128) for (int i = 0; i < 3; i++) push(bar_wq + i * 8, 0);
            push(early ? bar_e : bar_full, 0);
            next = claim();
            desc[0] = cta; desc[9] = 0;
#pragma unroll
            for (int i = 1; i < NBAR; i++) {
                const int o = i * 8;
                if (o >= 4 * NST * 8 && o < 4 * NST * 8 + 24) continue;
                if (o == 4 * NST * 8 + 48) continue;
                mbar_init(bar_full + o, bar_full + o == bar_ssum ? 4 : bar_full + o == bar_gdone ? 2 : 1);
            }
            asm volatile("fence.mbarrier_init.release.cluster;" ::: "memory");
        }
        __syncwarp();
        asm volatile("bar.arrive 3, %0;" :: "n"(NTHREADS) : "memory");
        if (lane == 0) {
            if (early) {
                for (int i = 1; i < 3; i++) { gate4(); col_piece(&maps.wg, eunit, i, sb, bar_e); }
                for (int i = 0; i < 3; i++) { gate4(); col_piece(&maps.wu, eunit, i, sb + STAGE, bar_e + 24); }
                for (int i = 0; i < 3; i++) { gate4(); down_piece(eunit, i, sb + 2 * STAGE, bar_e + 48); }
                const int tile = dyn_tile(next);
                gate4(); issue_k(tile, 3, 0); mbar_arrive(bar_first);
                next = claim();
                gate4(); issue_v(tile, 3, 0);
            } else {
                gate4(); issue_v(cta, 0, 0);
#pragma unroll
                for (int i = 1; i < NST; i++) { gate4(); issue_k(cta + i * NPLAIN, i, 0); gate4(); issue_v(cta + i * NPLAIN, i, 0); }
            }
            if (cta < 128) mbar_wait(bar_wfree, 0);
            if (cta < NLATE) for (int i = 0; i < 3; i++) { gate4(); col_piece(&maps.wg, cta, i, sb + SM_WBUF, bar_wg); }
            if (early) mbar_wait(bar_q + 24, 0);
            int st = 0; uint32_t ph = 0;
            while (true) {
                if (next < 0) {
                    Spin sp;
                    while (!mbar_test(fifo[F0] & ~1u, fifo[F0] & 1u)) {
                        if (desc[9] >= NDYN - PEEK && ld_relaxed1(&g_queue[0]) >= (unsigned)NDYN) { next = NDYN; break; }
                        __nanosleep(100);
                        sp.tick();
                    }
                    if (next >= NDYN) break;
                    mbar_wait(bar_empty + st * 8, ph);
                    next = claim();
                } else {
                    gate(1);
                    mbar_wait(bar_empty + st * 8, ph);
                }
                if (next >= NDYN) break;
                const int tile = dyn_tile(next);
                const uint32_t par = (early && st < 3) ? ph : ph ^ 1u;
                issue_k(tile, st, par);
                desc[9] = next;
                mbar_expect(bar_q + st * 8, 1024);
                bulk_g2s(sb + st * STAGE + 32768, g_q + (tile / TPP) * 256, 1024, bar_q + st * 8);
                next = next >= NDYN - LATECLAIM ? -1 : claim();
                if (next >= 0) gate(1);
                issue_v(tile, st, par);
                if (++st == NST) { st = 0; ph ^= 1; }
            }
            desc[9] = NDYN;
            const int stU = st;
            desc[4] = stU;
#pragma unroll
            for (int i = 0; i < F0; i++) fifo[i] = 0;
            int ends = 0, k = cta < NLATE ? 0 : 6;
            const int kend = cta < 128 ? 10 : 6;
            if (cta < NLATE) mbar_wait(bar_gdone, 0);
            Spin sp;
            while (ends < NST || k < kend) {
                if (ends < NST && mbar_test(bar_empty + st * 8, ph)) {
#pragma unroll
                    for (int i = 0; i < FN; i++) if ((fifo[i] & ~1u) == bar_full + st * 8) fifo[i] = 0;
                    desc[st] = -1;
                    mbar_arrive(bar_full + st * 8);
                    if (++st == NST) { st = 0; ph ^= 1; }
                    ends++;
                }
                const uint32_t f = fifo[FN - EPIECES];
                if (k < kend && ends >= (k < 3 ? 1 : k < 6 ? 2 : 0) && (f == 0 || mbar_test(f & ~1u, f & 1u))) {
                    if (k < 3) col_piece(&maps.wu, cta, k, sb + stU * STAGE, bar_lu);
                    else if (k < 6) down_piece(cta, k - 3, sb + ((stU + 1) % NST) * STAGE, bar_ld);
                    else piece(&maps.wo, (cta & 7) * 72, (cta >> 3) * 256 + (k - 6) * 64, sb + SM_WBUF + (k - 6) * 9216, bar_wo + (k - 6) * 8, 9216);
                    k++;
                }
                sp.tick();
            }
            if (atomicAdd(&g_state[0], 1u) == NCTA - 1) {
                g_queue[0] = 0; g_state[0] = 0;
                g_state[1] = g_state[1] + 1;
            }
        }
    } else if (warp < NST) {
        const int g = lane >> 2, t = lane & 3;
        float xfin = 0.f;
        if (tid < 36 && cta < 128) xfin = __bfloat162float(x[cta * 36 + tid]);
        {
#pragma unroll
            for (int r = 0; r < 2; r++) {
                float v[18], s = 0.f;
#pragma unroll
                for (int i = 0; i < 9; i++) { v[2 * i] = __uint_as_float(xr[r][i] << 16); v[2 * i + 1] = __uint_as_float(xr[r][i] & 0xFFFF0000u); s += v[2 * i] + v[2 * i + 1]; }
#pragma unroll
                for (int o = 16; o; o >>= 1) s += __shfl_xor_sync(~0u, s, o);
                const float mean = s * (1.0f / DM);
                float q = 0.f;
#pragma unroll
                for (int i = 0; i < 18; i++) { float d = v[i] - mean; q += d * d; }
#pragma unroll
                for (int o = 16; o; o >>= 1) q += __shfl_xor_sync(~0u, q, o);
                const float mb = bfr(mean), rden = __frcp_rn(bfr(__fsqrt_rn(bfr(bfr(q * (1.0f / DM)) + 1e-5f))));
                uint32_t* xn = reinterpret_cast<uint32_t*>(sg + SM_XN) + (warp * 2 + r) * (XP / 2);
#pragma unroll
                for (int i = 0; i < 9; i++) xn[i * 32 + lane] = pack_bf16(bfr(v[2 * i] - mb) * rden, bfr(v[2 * i + 1] - mb) * rden);
            }
        }
        const uint32_t tag = (epoch & 1u) ^ 1u;
        asm volatile("bar.sync 3, %0;" :: "n"(NTHREADS), "r"(tag) : "memory");
        if (cta < 128) {
            float acc[4];
            const int mt = warp & 1, kh = warp >> 1;
            proj32<18>(acc, sb + SM_WBUF, bar_wq, sb + SM_XN, lane, mt, kh * 18);
            float* gu = reinterpret_cast<float*>(sg + SM_GU);
            put_frag(gu + kh * 288, acc, mt, g, t);
            bar_cons();
            {
                const int b = tid >> 4, c = (tid & 15) * 2;
                const float q0 = gu[b * 36 + c] + gu[(8 + b) * 36 + c], q1 = gu[b * 36 + c + 1] + gu[(8 + b) * 36 + c + 1];
                const int hq = cta >> 2, d = (cta & 3) * 32 + c;
                const int off = (b * HKV + (hq >> 1)) * 256 + (hq & 1) * 128 + (d >> 4) * 16 + ((d & 7) >> 1) * 4 + ((d >> 3) & 1) * 2;
                const uint32_t pk = pack_bf16(q0, q1);
                st_relaxed2(g_q + off, (pk << 16) | tag, (pk & 0xFFFF0000u) | tag);
            }
            bar_cons();
            if (tid == 0) mbar_arrive(bar_wfree);
        }
        if (cta >= NPLAIN) {
            ffn_unit<false>(sb, sb, sb + STAGE, sb + 2 * STAGE, bar_e, bar_e + 24, bar_e + 48, NLATE + cta - NPLAIN, warp, lane, tag);
            bar_cons();
            if (warp < 3 && lane == 0) mbar_arrive(bar_empty + warp * 8);
        }
        const uint32_t kb = sb + warp * STAGE, vb = kb + 16384, qb = kb + 32768;
        const int mat = lane >> 3, r8 = lane & 7;
        const int kkey = (mat & 1) ? 8 + ((r8 + 4) & 7) : r8;
        const int rho = (r8 >> 1) + (mat >> 1) * 4;
        const int vkey = (r8 & 1) ? 8 + ((rho + 4) & 7) : rho;
        const float sc = 1.4426950408889634f;
        uint32_t ph = 0;
        while (true) {
            mbar_wait(bar_full + warp * 8, ph);
            ph ^= 1;
            const int tile = desc[warp];
            if (tile < 0) break;
            mbar_wait(bar_q + warp * 8, ph ^ 1u);
            uint32_t qf[16];
            {
                const bool on = (g == 0) || (g == 2);
                uint4 v[8];
                uint32_t bad = 0;
#pragma unroll
                for (int j = 0; j < 8; j++) {
                    v[j] = make_uint4(tag, tag, tag, tag);
                    if (on) v[j] = lds128(qb + (g >> 1) * 512 + j * 64 + t * 16);
                    bad |= (v[j].x ^ tag) | (v[j].y ^ tag) | (v[j].z ^ tag) | (v[j].w ^ tag);
                }
                if (__any_sync(~0u, bad & 1u)) {
                    Spin sp;
                    do {
                        bad = 0;
                        if (on) {
#pragma unroll
                            for (int j = 0; j < 8; j++) v[j] = ld_relaxed4(g_q + (tile / TPP) * 256 + (g >> 1) * 128 + j * 16 + t * 4);
#pragma unroll
                            for (int j = 0; j < 8; j++) bad |= bad4(v[j], tag);
                        }
                        sp.tick();
                    } while (__any_sync(~0u, bad));
                }
#pragma unroll
                for (int j = 0; j < 8; j++) { qf[2 * j] = __byte_perm(v[j].x, v[j].y, 0x7632); qf[2 * j + 1] = __byte_perm(v[j].z, v[j].w, 0x7632); }
            }
            float s[4][4];
#pragma unroll
            for (int mt = 0; mt < 4; mt++) { s[mt][0] = s[mt][1] = s[mt][2] = s[mt][3] = 0.f; }
#pragma unroll
            for (int ks = 0; ks < 8; ks++)
#pragma unroll
                for (int mt = 0; mt < 4; mt++) {
                    uint32_t a[4];
                    ldsm4(a, addr_kv(kb, mt * 16 + kkey, 2 * ks + (mat >> 1)));
                    mma16816(s[mt], a, qf[2 * ks], qf[2 * ks + 1]);
                }
#pragma unroll
            for (int mt = 0; mt < 4; mt++) {
                const uint32_t r1 = pack_bf16(s[mt][0], s[mt][2]);
                const uint32_t r2 = pack_bf16(__uint_as_float(r1 << 16) * 0.08838834764831845f, __uint_as_float(r1 & 0xFFFF0000u) * 0.08838834764831845f);
                s[mt][0] = __uint_as_float(r2 << 16); s[mt][2] = __uint_as_float(r2 & 0xFFFF0000u);
            }
            float m = fmaxf(fmaxf(fmaxf(s[0][0], s[0][2]), fmaxf(s[1][0], s[1][2])), fmaxf(fmaxf(s[2][0], s[2][2]), fmaxf(s[3][0], s[3][2])));
            m = fmaxf(m, __shfl_xor_sync(~0u, m, 4));
            m = fmaxf(m, __shfl_xor_sync(~0u, m, 8));
            m = fmaxf(m, __shfl_xor_sync(~0u, m, 16));
            const float ms = untagf(__float_as_uint(m * sc));
            float l = 0.f;
            uint32_t pb[4][2];
#pragma unroll
            for (int mt = 0; mt < 4; mt++) {
                const float p0 = ex2(fmaf(s[mt][0], sc, -ms)), p1 = ex2(fmaf(s[mt][2], sc, -ms));
                l += p0 + p1;
                const uint32_t pk = pack_bf16(p0, p1);
                pb[mt][0] = __shfl_sync(~0u, pk, 4 * t + (g & 1));
                pb[mt][1] = __shfl_sync(~0u, pk, 4 * (t + 4) + (g & 1));
            }
            l += __shfl_xor_sync(~0u, l, 4);
            l += __shfl_xor_sync(~0u, l, 8);
            l += __shfl_xor_sync(~0u, l, 16);
            float o[8][4];
#pragma unroll
            for (int i = 0; i < 8; i++) { o[i][0] = o[i][1] = o[i][2] = o[i][3] = 0.f; }
            mbar_wait(bar_v + warp * 8, ph ^ 1u);
#pragma unroll
            for (int kk = 0; kk < 4; kk++)
#pragma unroll
                for (int i = 0; i < 8; i++) {
                    uint32_t a[4];
                    ldsm4t(a, addr_kv(vb, kk * 16 + vkey, 2 * i + (mat & 1)));
                    mma16816(o[i], a, pb[kk][0], pb[kk][1]);
                }
            __syncwarp();
            if (lane == 0) mbar_arrive(bar_empty + warp * 8);
            const float inv = __fdividef(1.0f, l);
            const float inv1 = __shfl_down_sync(~0u, inv, 1);
            const int pair = tile / TPP, tt = tile % TPP;
            if (t == 0) {
                uint2* dst = g_po + ((size_t)pair * 8 * TPP + tt) * 8 + g;
#pragma unroll
                for (int qd = 0; qd < 4; qd++) {
                    st_relaxed2(dst + (size_t)qd * TPP * 8,
                                pack_tag(o[2 * qd][0] * inv, o[2 * qd][2] * inv, tag), pack_tag(o[2 * qd + 1][0] * inv, o[2 * qd + 1][2] * inv, tag));
                    st_relaxed2(dst + (size_t)(4 + qd) * TPP * 8,
                                pack_tag(o[2 * qd][1] * inv1, o[2 * qd][3] * inv1, tag), pack_tag(o[2 * qd + 1][1] * inv1, o[2 * qd + 1][3] * inv1, tag));
                }
            }
            {
                const uint32_t m_ = tagf(ms, tag), l_ = tagf(l, tag);
                const uint32_t m0 = __shfl_sync(~0u, m_, 0), l0 = __shfl_sync(~0u, l_, 0), m1 = __shfl_sync(~0u, m_, 1), l1 = __shfl_sync(~0u, l_, 1);
                if (lane < 2) st_relaxed4(g_ml + tile * 2 + lane, m0, l0, m1, l1);
            }
        }
        if (cta < NLATE) {
            {
                const uint32_t inv = tag ^ 1u;
                put_tile(fp_slot(cta, warp, g, t), inv, inv, inv, inv, true);
                if (warp < 2) st_relaxed4(g_h + (cta * 2 + warp) * 32 + lane, inv, inv, inv, inv);
            }
            const int stU = desc[4];
            ffn_unit<true>(sb, 0, sb + stU * STAGE, sb + ((stU + 1) % NST) * STAGE, bar_gdone, bar_lu, bar_ld, cta, warp, lane, tag);
        }
        if (cta < 128) {
            float* red = reinterpret_cast<float*>(sg + SM_RED);
            gather16(g_fp + cta * 36, red, tid, tag);
            bar_cons();
            if (tid < 36) {
                const float f = (red[tid] + red[36 + tid]) + (red[72 + tid] + red[108 + tid]);
                const float gate = bfr(silu_f(bfr(f)));
                mbar_wait(bar_ssum, 0);
                const float s = bfr((red[144 + tid] + red[180 + tid]) + (red[216 + tid] + red[252 + tid]));
                out[cta * 36 + tid] = __float2bfloat16_rn(xfin + bfr(s * gate));
            }
        }
    } else {
        const int cw = warp - NST - 1, ctid = tid - (NST + 1) * 32;
        const uint32_t tag = (epoch & 1u) ^ 1u;
        {
            const bool early = cta >= NPLAIN;
            asm volatile("bar.sync 3, %0;" :: "n"(NTHREADS), "r"(tag) : "memory");
            if (!early || cw == 3) {
                int tile = cta + cw * NPLAIN;
                if (early) {
                    mbar_wait(bar_first, 0);
                    tile = desc[3];
                } else {
                    mbar_wait(bar_wfree, 0);
                    __nanosleep(QDELAY);
                }
                const uint32_t* src = g_q + (tile / TPP) * 256 + lane * 4;
                uint4 v0, v1;
                Spin sp;
                while (true) {
                    v0 = ld_relaxed4(src); v1 = ld_relaxed4(src + 128);
                    if (!__any_sync(~0u, bad4(v0, tag) | bad4(v1, tag))) break;
                    __nanosleep(200);
                    sp.tick();
                }
                uint4* dst = reinterpret_cast<uint4*>(sg + cw * STAGE + 32768) + lane;
                dst[0] = v0; dst[32] = v1;
                __syncwarp();
                if (lane == 0) mbar_arrive(bar_q + cw * 8);
            }
            if (cw < 2 && cta < NLATE) {
                float acc[4];
                proj32<36>(acc, sb + SM_WBUF, bar_wg, sb + SM_XN, lane, cw, 0);
                put_frag(reinterpret_cast<float*>(sg + SM_GL), acc, cw, lane >> 2, lane & 3);
                __syncwarp();
                if (lane == 0) mbar_arrive(bar_gdone);
            }
        }
        if (cta < 128) {
            const int g = lane >> 2, t = lane & 3;
            const int hkv = cta >> 3, head = (cta >> 2) & 1, qd = cta & 3;
            uint32_t* sdst = g_sp + (hkv * NB + 2 * t) * DM + (cta & 7) * 72 + cw * 16 + g;
            const uint4* oxs = g_ox + (hkv * 8 * NB + g) * 8 + t;
            uint32_t ob[16][2];
            auto collect_o = [&](bool on) {
                uint4 v[16];
                Spin sp;
                while (true) {
                    uint32_t bad = 0;
                    if (on) {
#pragma unroll
                        for (int i = 0; i < 16; i++) v[i] = ld_relaxed4(oxs + (i >> 1) * (NB * 8) + (i & 1) * 4);
#pragma unroll
                        for (int i = 0; i < 16; i++) bad |= bad4(v[i], tag);
                    }
                    if (!__any_sync(~0u, bad)) break;
                    __nanosleep(30);
                    sp.tick();
                }
                if (on) {
#pragma unroll
                    for (int i = 0; i < 16; i++) { ob[i][0] = __byte_perm(v[i].x, v[i].y, 0x7632); ob[i][1] = __byte_perm(v[i].z, v[i].w, 0x7632); }
                }
            };
#pragma unroll 1
            for (int b = 0; b < NB; b++) {
                const int p = b * HKV + hkv;
                uint2 e;
                uint4 v[4];
                const uint2* rows = g_po + ((size_t)((p * 2 + head) * 4 + qd) * TPP + cw * 32 + g) * 8 + t * 2;
                {
                    const uint2* mlp = reinterpret_cast<const uint2*>(g_ml + (p * TPP + cw * 32 + lane) * 2) + head;
                    Spin sp;
                    const int plast = (p + 1) * TPP - NPLAIN * NST;
                                        const int target = min(plast + MARGIN, NDYN - TAILPOLL);
                    while (desc[9] < target) { __nanosleep(250); sp.tick(); }
                    if (b == NB - 1) collect_o(g < NB - 1);
                    while (true) {
                        e = ld_relaxed2(mlp);
                        const uint32_t miss = __ballot_sync(~0u, ((e.x ^ tag) | (e.y ^ tag)) & 1u);
                        if (!miss) break;
                        __nanosleep(miss == ~0u ? 300 : 20);
                        sp.tick();
                    }
                }
#pragma unroll
                for (int i = 0; i < 4; i++) v[i] = ld_relaxed4(rows + i * 64);
                const float m = untagf(e.x);
                float M = m;
#pragma unroll
                for (int o = 16; o; o >>= 1) M = fmaxf(M, __shfl_xor_sync(~0u, M, o));
                const float w = ex2(m - M) * untagf(e.y);
                float L = w;
#pragma unroll
                for (int o = 16; o; o >>= 1) L += __shfl_xor_sync(~0u, L, o);
                float wr[4];
#pragma unroll
                for (int i = 0; i < 4; i++) wr[i] = __shfl_sync(~0u, w, i * 8 + g);
                {
                    Spin sp;
                    while (__any_sync(~0u, bad4(v[0], tag) | bad4(v[1], tag) | bad4(v[2], tag) | bad4(v[3], tag))) {
#pragma unroll
                        for (int i = 0; i < 4; i++) v[i] = ld_relaxed4(rows + i * 64);
                        sp.tick();
                    }
                }
                float acc[8];
#pragma unroll
                for (int k = 0; k < 8; k++) acc[k] = 0.f;
#pragma unroll
                for (int i = 0; i < 4; i++) {
                    const uint32_t u[4] = {v[i].x, v[i].y, v[i].z, v[i].w};
#pragma unroll
                    for (int k = 0; k < 4; k++) {
                        acc[2 * k] = fmaf(wr[i], __uint_as_float((u[k] << 16) & 0xFFFE0000u), acc[2 * k]);
                        acc[2 * k + 1] = fmaf(wr[i], __uint_as_float(u[k] & 0xFFFF0000u), acc[2 * k + 1]);
                    }
                }
#pragma unroll
                for (int k = 0; k < 8; k++) {
                    acc[k] += __shfl_xor_sync(~0u, acc[k], 4);
                    acc[k] += __shfl_xor_sync(~0u, acc[k], 8);
                    acc[k] += __shfl_xor_sync(~0u, acc[k], 16);
                }
                float* part = reinterpret_cast<float*>(sg + SM_PART) + (b & 1) * 160;
                if (g == 0) {
#pragma unroll
                    for (int k = 0; k < 4; k++) *reinterpret_cast<float2*>(part + cw * 40 + k * 8 + 2 * t) = make_float2(acc[k], acc[k + 4]);
                    if (t == 0) *reinterpret_cast<float2*>(part + cw * 40 + 32) = make_float2(M, L);
                }
                bar_comb();
                if (ctid < 8) {
                    float2 ml4[4];
#pragma unroll
                    for (int i = 0; i < 4; i++) ml4[i] = *reinterpret_cast<const float2*>(part + i * 40 + 32);
                    const float MM = fmaxf(fmaxf(ml4[0].x, ml4[1].x), fmaxf(ml4[2].x, ml4[3].x));
                    float sw[4], LL = 0.f;
#pragma unroll
                    for (int i = 0; i < 4; i++) { sw[i] = ex2(ml4[i].x - MM); LL = fmaf(sw[i], ml4[i].y, LL); }
                    const float inv = 1.0f / LL;
                    uint32_t pk[2];
#pragma unroll
                    for (int j = 0; j < 2; j++) {
                        float o0 = 0.f, o1 = 0.f;
#pragma unroll
                        for (int i = 0; i < 4; i++) {
                            const float2 pv = *reinterpret_cast<const float2*>(part + i * 40 + g * 16 + j * 8 + 2 * t);
                            o0 = fmaf(sw[i], pv.x, o0); o1 = fmaf(sw[i], pv.y, o1);
                        }
                        pk[j] = pack_bf16(o0 * inv, o1 * inv);
                    }
                    uint4* dst = g_ox + (cta * NB + b) * 8 + ctid;
                    st_relaxed4(dst, (pk[0] << 16) | tag, (pk[0] & 0xFFFF0000u) | tag, (pk[1] << 16) | tag, (pk[1] & 0xFFFF0000u) | tag);
                    if (b == NB - 2) st_relaxed4(dst + 8, tag ^ 1u, tag ^ 1u, tag ^ 1u, tag ^ 1u);
                }
                if (b == NB - 2) {
                    const uint32_t inv = tag ^ 1u;
                    put_tile(sdst, inv, inv, inv, inv, true);
                    if (cw == 0) put_tile(sdst + 64, inv, inv, inv, inv, false);
                }
                __syncwarp();
            }
            {
                __nanosleep(ODELAY);
                const int m4 = lane >> 3;
                const uint32_t a0 = sb + SM_WBUF + ((m4 >> 1) * 8 + (lane & 7)) * 144 + (m4 & 1) * 16;
                uint32_t a[16][4], a2[4][4];
                auto load_a = [&]() {
#pragma unroll
                    for (int ks = 0; ks < 16; ks++) ldsm4t(a[ks], a0 + ks * (16 * 144) + cw * 32);
#pragma unroll
                    for (int i = 0; i < 4; i++) ldsm4t(a2[i], a0 + (cw * 4 + i) * (16 * 144) + 128);
                };
                bool have_a = false;
                const uint4* src = g_ox + ((hkv * 8 + (lane >> 3)) * NB + NB - 1) * 8 + (lane & 7);
                uint4 v0, v1;
                Spin sp;
                while (true) {
                    v0 = ld_relaxed4(src); v1 = ld_relaxed4(src + 4 * NB * 8);
                    if (!have_a && mbar_test(bar_wo, 0) && mbar_test(bar_wo + 8, 0) && mbar_test(bar_wo + 16, 0) && mbar_test(bar_wo + 24, 0)) { load_a(); have_a = true; }
                    if (!__any_sync(~0u, bad4(v0, tag) | bad4(v1, tag))) break;
                    sp.tick();
                }
                {
                    uint4* ox = reinterpret_cast<uint4*>(sg + SM_OB) + cw * 32;
                    ox[(lane & 3) * 8 + (lane >> 2)] = make_uint4(__byte_perm(v0.x, v0.y, 0x7632), __byte_perm(v0.z, v0.w, 0x7632),
                                                                  __byte_perm(v1.x, v1.y, 0x7632), __byte_perm(v1.z, v1.w, 0x7632));
                    __syncwarp();
                    if (g == NB - 1) {
#pragma unroll
                        for (int i = 0; i < 8; i++) { const uint4 w4 = ox[t * 8 + i]; ob[i][0] = w4.x; ob[i][1] = w4.y; ob[8 + i][0] = w4.z; ob[8 + i][1] = w4.w; }
                    }
                }
                float c0[4] = {0.f, 0.f, 0.f, 0.f}, c1[4] = {0.f, 0.f, 0.f, 0.f}, c2[4] = {0.f, 0.f, 0.f, 0.f};
                uint32_t b2[4][2];
#pragma unroll
                for (int i = 0; i < 4; i++) {
                    b2[i][0] = cw == 0 ? ob[i][0] : cw == 1 ? ob[4 + i][0] : cw == 2 ? ob[8 + i][0] : ob[12 + i][0];
                    b2[i][1] = cw == 0 ? ob[i][1] : cw == 1 ? ob[4 + i][1] : cw == 2 ? ob[8 + i][1] : ob[12 + i][1];
                }
                if (have_a) {
#pragma unroll
                    for (int i = 0; i < 4; i++) mma16816(c2, a2[i], b2[i][0], b2[i][1]);
#pragma unroll
                    for (int ks = 0; ks < 16; ks++) mma16816((ks & 1) ? c1 : c0, a[ks], ob[ks][0], ob[ks][1]);
                } else {
#pragma unroll
                    for (int pc = 0; pc < 4; pc++) {
                        mbar_wait(bar_wo + pc * 8, 0);
#pragma unroll
                        for (int i = 0; i < 4; i++) ldsm4t(a[i], a0 + (pc * 4 + i) * (16 * 144) + cw * 32);
                        if (pc == cw) {
#pragma unroll
                            for (int i = 0; i < 4; i++) ldsm4t(a2[i], a0 + (pc * 4 + i) * (16 * 144) + 128);
#pragma unroll
                            for (int i = 0; i < 4; i++) mma16816(c2, a2[i], b2[i][0], b2[i][1]);
                        }
#pragma unroll
                        for (int i = 0; i < 4; i++) mma16816((i & 1) ? c1 : c0, a[i], ob[pc * 4 + i][0], ob[pc * 4 + i][1]);
                    }
                }
                float2* x4 = reinterpret_cast<float2*>(sg + SM_PART);
                x4[cw * 32 + lane] = make_float2(c2[0], c2[1]);
                put_tile(sdst, tagf(c0[0] + c1[0], tag), tagf(c0[1] + c1[1], tag), tagf(c0[2] + c1[2], tag), tagf(c0[3] + c1[3], tag), true);
                bar_comb();
                if (cw == 0) {
                    const float2 p0 = x4[lane], p1 = x4[32 + lane], p2 = x4[64 + lane], p3 = x4[96 + lane];
                    put_tile(sdst + 64, tagf((p0.x + p1.x) + (p2.x + p3.x), tag), tagf((p0.y + p1.y) + (p2.y + p3.y), tag), 0, 0, false);
                }
            }
            gather16(g_sp + cta * 36, reinterpret_cast<float*>(sg + SM_RED) + 144, ctid, tag);
            __syncwarp();
            if (lane == 0) mbar_arrive(bar_ssum);
        }
    }
}

#define f_q (reinterpret_cast<float*>(g_po))
#define f_o (f_q + NB * 4096)
#define f_h (f_o + NB * 4096)

__global__ void fb_proj(const __nv_bfloat16* x, const __nv_bfloat16* wq, const __nv_bfloat16* wg, const __nv_bfloat16* wu) {
    __shared__ float xn[DM];
    const int b = blockIdx.y, n = blockIdx.x * blockDim.x + threadIdx.x;
    float s = 0.f, q = 0.f;
    for (int i = 0; i < DM; i++) s += __bfloat162float(x[b * DM + i]);
    const float mean = s / DM;
    for (int i = 0; i < DM; i++) { const float d = __bfloat162float(x[b * DM + i]) - mean; q += d * d; }
    const float den = bfr(sqrtf(bfr(bfr(q / DM) + 1e-5f)));
    for (int i = threadIdx.x; i < DM; i += blockDim.x) xn[i] = bfr(bfr(__bfloat162float(x[b * DM + i]) - bfr(mean)) / den);
    __syncthreads();
    if (n < 4096) {
        float a = 0.f;
        for (int k = 0; k < DM; k++) a += xn[k] * __bfloat162float(wq[(size_t)k * 4096 + n]);
        f_q[b * 4096 + n] = bfr(a);
    }
    if (n < FF) {
        float g = 0.f, u = 0.f;
        for (int k = 0; k < DM; k++) { g += xn[k] * __bfloat162float(wg[(size_t)k * FF + n]); u += xn[k] * __bfloat162float(wu[(size_t)k * FF + n]); }
        f_h[b * FF + n] = bfr(bfr(silu_f(bfr(g))) * bfr(u));
    }
}
__global__ void fb_attn(const __nv_bfloat16* K, const __nv_bfloat16* V) {
    __shared__ float sc[SK], red[128];
    const int t = threadIdx.x, b = blockIdx.x >> 5, h = blockIdx.x & 31;
    const __nv_bfloat16* k = K + (size_t)(b * HKV + (h >> 1)) * SK * 128;
    const __nv_bfloat16* v = V + (size_t)(b * HKV + (h >> 1)) * SK * 128;
    const float* q = f_q + b * 4096 + h * 128;
    float m = -INFINITY, l = 0.f, o = 0.f;
    for (int j = t; j < SK; j += 128) {
        float s = 0.f;
        for (int d = 0; d < 128; d++) s += q[d] * __bfloat162float(k[(size_t)j * 128 + d]);
        sc[j] = bfr(bfr(s) * 0.08838834764831845f); m = fmaxf(m, sc[j]);
    }
    red[t] = m; __syncthreads();
    for (int i = 0; i < 128; i++) m = fmaxf(m, red[i]);
    __syncthreads();
    for (int j = t; j < SK; j += 128) { sc[j] = __expf(sc[j] - m); l += sc[j]; }
    red[t] = l; __syncthreads();
    l = 0.f;
    for (int i = 0; i < 128; i++) l += red[i];
    for (int j = 0; j < SK; j++) o += sc[j] * __bfloat162float(v[(size_t)j * 128 + t]);
    f_o[b * 4096 + h * 128 + t] = bfr(o / l);
}
__global__ void fb_out(const __nv_bfloat16* x, const __nv_bfloat16* wo, const __nv_bfloat16* wd, __nv_bfloat16* out) {
    const int b = blockIdx.y, n = blockIdx.x * blockDim.x + threadIdx.x;
    float s = 0.f, f = 0.f;
    for (int k = 0; k < 4096; k++) s += f_o[b * 4096 + k] * __bfloat162float(wo[(size_t)k * DM + n]);
    for (int k = 0; k < FF; k++) f += f_h[b * FF + k] * __bfloat162float(wd[(size_t)k * DM + n]);
    out[b * DM + n] = __float2bfloat16_rn(__bfloat162float(x[b * DM + n]) + bfr(bfr(s) * bfr(silu_f(bfr(f)))));
}

typedef CUresult (*EncodeFn)(CUtensorMap*, CUtensorMapDataType, cuuint32_t, void*, const cuuint64_t*, const cuuint64_t*,
                             const cuuint32_t*, const cuuint32_t*, CUtensorMapInterleave, CUtensorMapSwizzle,
                             CUtensorMapL2promotion, CUtensorMapFloatOOBfill);

void make_map(EncodeFn enc, CUtensorMap* m, const void* p, int rank, const cuuint64_t* dims, const cuuint64_t* strides,
              const cuuint32_t* box, CUtensorMapSwizzle sw, CUtensorMapL2promotion promo) {
    cuuint32_t es[3] = {1, 1, 1};
    enc(m, CU_TENSOR_MAP_DATA_TYPE_BFLOAT16, rank, const_cast<void*>(p), dims, strides, box, es,
        CU_TENSOR_MAP_INTERLEAVE_NONE, sw, promo, CU_TENSOR_MAP_FLOAT_OOB_FILL_NONE);
}

}

extern "C" void kernel_launch(void* const* d_in, const int* in_sizes, int n_in, void* d_out, int out_size) {
    (void)in_sizes; (void)n_in; (void)out_size;
    static EncodeFn enc = nullptr;
    static int mode = 0;
    if (!mode) {
        void* fn = nullptr;
        cudaDriverEntryPointQueryResult qr;
        cudaGetDriverEntryPoint("cuTensorMapEncodeTiled", &fn, cudaEnableDefault, &qr);
        enc = (EncodeFn)fn;
        int dev = 0, sms = 0, occ = 0;
        cudaGetDevice(&dev);
        cudaDeviceGetAttribute(&sms, cudaDevAttrMultiProcessorCount, dev);
        cudaFuncSetAttribute(fused_decode_kernel, cudaFuncAttributeMaxDynamicSharedMemorySize, SMEM_BYTES);
        cudaOccupancyMaxActiveBlocksPerMultiprocessor(&occ, fused_decode_kernel, NTHREADS, SMEM_BYTES);
        mode = (enc && occ * sms >= NCTA) ? 1 : 2;
    }
    typedef const __nv_bfloat16* P;
    if (mode == 2) {
        fb_proj<<<dim3(FF / 128, NB), 128>>>((P)d_in[0], (P)d_in[3], (P)d_in[6], (P)d_in[7]);
        fb_attn<<<NB * 32, 128>>>((P)d_in[1], (P)d_in[2]);
        fb_out<<<dim3(DM / 64, NB), 64>>>((P)d_in[0], (P)d_in[4], (P)d_in[8], (__nv_bfloat16*)d_out);
        return;
    }
    Maps maps;
    const cuuint64_t kvrows = (cuuint64_t)NPAIR * SK;
    for (int i = 0; i < 2; i++) {
        cuuint64_t dims[3] = {64, kvrows, 2}, strides[2] = {256, 128};
        cuuint32_t box[3] = {64, TILE, 2};
        make_map(enc, i ? &maps.v : &maps.k, d_in[1 + i], 3, dims, strides, box, CU_TENSOR_MAP_SWIZZLE_128B, CU_TENSOR_MAP_L2_PROMOTION_L2_256B);
    }
    {
        cuuint32_t box[2] = {32, 192};
        cuuint64_t dq[2] = {4096, DM}, sq[1] = {4096 * 2};
        make_map(enc, &maps.wq, d_in[3], 2, dq, sq, box, CU_TENSOR_MAP_SWIZZLE_64B, CU_TENSOR_MAP_L2_PROMOTION_L2_128B);
        cuuint64_t df[2] = {FF, DM}, sf[1] = {FF * 2};
        make_map(enc, &maps.wg, d_in[6], 2, df, sf, box, CU_TENSOR_MAP_SWIZZLE_64B, CU_TENSOR_MAP_L2_PROMOTION_L2_128B);
        make_map(enc, &maps.wu, d_in[7], 2, df, sf, box, CU_TENSOR_MAP_SWIZZLE_64B, CU_TENSOR_MAP_L2_PROMOTION_L2_128B);
    }
    {
        cuuint32_t boxo[2] = {72, 64};
        cuuint64_t d_o[2] = {DM, 4096}, s_o[1] = {DM * 2};
        make_map(enc, &maps.wo, d_in[4], 2, d_o, s_o, boxo, CU_TENSOR_MAP_SWIZZLE_NONE, CU_TENSOR_MAP_L2_PROMOTION_L2_128B);
        cuuint32_t boxd[2] = {64, 96};
        cuuint64_t d_d[2] = {DM, FF}, s_d[1] = {DM * 2};
        make_map(enc, &maps.wd, d_in[8], 2, d_d, s_d, boxd, CU_TENSOR_MAP_SWIZZLE_128B, CU_TENSOR_MAP_L2_PROMOTION_L2_128B);
    }
    fused_decode_kernel<<<NCTA, NTHREADS, SMEM_BYTES>>>(maps, (const __nv_bfloat16*)d_in[0], (__nv_bfloat16*)d_out);
}
```

```cpp
#include <cuda_runtime.h>
#include <cuda_bf16.h>
#include <cuda.h>
#include <math.h>
#include <stdint.h>

namespace {

constexpr int NB = 8, DM = 576, HKV = 16, SK = 8192, FF = 4608;
constexpr int NPAIR = NB * HKV;
constexpr int TILE = 64;
constexpr int TPP = SK / TILE;
constexpr int NKV = NPAIR * TPP;
constexpr int NCTA = 132;
constexpr int NST = 4;
constexpr int STAGE = 36864;
constexpr int NUNIT = FF / 32;
constexpr int GRP = 9;
constexpr int NGRP = NUNIT / GRP;
constexpr int NLATE = (NCTA / GRP) * GRP;
constexpr int NEARLY = NUNIT - NLATE;
constexpr int NPLAIN = NCTA - NEARLY;
constexpr int NDYN = NKV - NPLAIN * NST;
constexpr int XP = 584;
constexpr int NTHREADS = 288;

constexpr int INFLIGHT = 3;
constexpr int SPIECES = 4;
constexpr int EPIECES = 4;
constexpr int LATECLAIM = 400;
constexpr int PEEK = 200;
constexpr int MARGIN = 600;
constexpr int TAILPOLL = 900;
constexpr int QDELAY = 800, HDELAY = 700, ODELAY = 400;

constexpr int SM_WBUF = NST * STAGE;
constexpr int SM_XN = SM_WBUF + STAGE;
constexpr int SM_GU = SM_XN + NB * XP * 2;
constexpr int SM_GL = SM_GU + 2 * 8 * 36 * 4;
constexpr int SM_HB = SM_GL + 8 * 36 * 4;
constexpr int SM_RED = SM_HB + 2 * GRP * 32 * 8;
constexpr int SM_PART = SM_RED + 9 * 36 * 4 + 12 * 4;
static_assert(SM_PART % 16 == 0, "");
constexpr int SM_OB = SM_PART + 2 * 4 * 40 * 4;
constexpr int SM_BAR = SM_OB + 4 * 512;
constexpr int NBAR = 4 * NST + 28;
constexpr int SM_DESC = SM_BAR + NBAR * 8;
constexpr int SM_TOTAL = SM_DESC + 64;
constexpr int SMEM_BYTES = SM_TOTAL + 1024;

struct Maps { CUtensorMap k, v, wq, wg, wu, wo, wd; };

__device__ __align__(128) unsigned g_queue[32];
__device__ __align__(128) unsigned g_state[32];
__device__ __align__(128) uint32_t g_q[NPAIR * 256];
__device__ __align__(128) uint4 g_ml[NKV * 2];
__device__ __align__(128) uint2 g_po[NPAIR * 2 * 4 * TPP * 8];
__device__ __align__(128) uint4 g_ox[128 * NB * 8];
__device__ __align__(128) uint32_t g_sp[HKV * NB * DM];
__device__ __align__(128) uint32_t g_fp[NGRP * NB * DM];
__device__ __align__(128) uint4 g_h[NUNIT * 2 * 32];

__device__ __forceinline__ uint32_t s2u(const void* p) { return (uint32_t)__cvta_generic_to_shared(p); }
__device__ __forceinline__ void mbar_init(uint32_t b, int c) { asm volatile("mbarrier.init.shared::cta.b64 [%0], %1;" :: "r"(b), "r"(c)); }
__device__ __forceinline__ void mbar_expect(uint32_t b, uint32_t bytes) { asm volatile("mbarrier.arrive.expect_tx.shared::cta.b64 _, [%0], %1;" :: "r"(b), "r"(bytes) : "memory"); }
__device__ __forceinline__ void mbar_arrive(uint32_t b) { asm volatile("mbarrier.arrive.shared::cta.b64 _, [%0];" :: "r"(b) : "memory"); }
__device__ __forceinline__ bool mbar_try(uint32_t b, uint32_t ph) {
    uint32_t ok;
    asm volatile("{\n.reg .pred p;\nmbarrier.try_wait.parity.shared::cta.b64 p, [%1], %2;\nselp.u32 %0, 1, 0, p;\n}" : "=r"(ok) : "r"(b), "r"(ph) : "memory");
    return ok != 0;
}
__device__ __forceinline__ bool mbar_test(uint32_t b, uint32_t ph) {
    uint32_t ok;
    asm volatile("{\n.reg .pred p;\nmbarrier.test_wait.parity.shared::cta.b64 p, [%1], %2;\nselp.u32 %0, 1, 0, p;\n}" : "=r"(ok) : "r"(b), "r"(ph) : "memory");
    return ok != 0;
}
constexpr long long SPIN_LIMIT = 4000000000LL;
__device__ __forceinline__ void mbar_wait(uint32_t b, uint32_t ph) {
    if (mbar_try(b, ph)) return;
    long long t0 = clock64();
    while (!mbar_try(b, ph)) { if (clock64() - t0 > SPIN_LIMIT) __trap(); }
}
struct Spin {
    long long t0 = 0;
    __device__ __forceinline__ void tick() { long long t = clock64(); if (t0 == 0) t0 = t; else if (t - t0 > SPIN_LIMIT) __trap(); }
};
__device__ __forceinline__ void bulk_g2s(uint32_t dst, const void* src, uint32_t bytes, uint32_t bar) {
    asm volatile("cp.async.bulk.shared::cluster.global.mbarrier::complete_tx::bytes [%0], [%1], %2, [%3];" :: "r"(dst), "l"(src), "r"(bytes), "r"(bar) : "memory");
}
__device__ __forceinline__ void tma2d(uint32_t dst, const CUtensorMap* m, int c0, int c1, uint32_t bar) {
    asm volatile("cp.async.bulk.tensor.2d.shared::cluster.global.mbarrier::complete_tx::bytes [%0], [%1, {%3, %4}], [%2];" :: "r"(dst), "l"(m), "r"(bar), "r"(c0), "r"(c1) : "memory");
}
__device__ __forceinline__ void tma3d(uint32_t dst, const CUtensorMap* m, int c0, int c1, int c2, uint32_t bar, uint64_t pol) {
    asm volatile("cp.async.bulk.tensor.3d.shared::cluster.global.mbarrier::complete_tx::bytes.L2::cache_hint [%0], [%1, {%3, %4, %5}], [%2], %6;" :: "r"(dst), "l"(m), "r"(bar), "r"(c0), "r"(c1), "r"(c2), "l"(pol) : "memory");
}
__device__ __forceinline__ void ldsm4(uint32_t (&r)[4], uint32_t a) {
    asm volatile("ldmatrix.sync.aligned.m8n8.x4.shared.b16 {%0,%1,%2,%3}, [%4];" : "=r"(r[0]), "=r"(r[1]), "=r"(r[2]), "=r"(r[3]) : "r"(a));
}
__device__ __forceinline__ void ldsm4t(uint32_t (&r)[4], uint32_t a) {
    asm volatile("ldmatrix.sync.aligned.m8n8.x4.trans.shared.b16 {%0,%1,%2,%3}, [%4];" : "=r"(r[0]), "=r"(r[1]), "=r"(r[2]), "=r"(r[3]) : "r"(a));
}
__device__ __forceinline__ void mma16816(float (&c)[4], const uint32_t (&a)[4], uint32_t b0, uint32_t b1) {
    asm("mma.sync.aligned.m16n8k16.row.col.f32.bf16.bf16.f32 {%0,%1,%2,%3}, {%4,%5,%6,%7}, {%8,%9}, {%0,%1,%2,%3};"
                 : "+f"(c[0]), "+f"(c[1]), "+f"(c[2]), "+f"(c[3]) : "r"(a[0]), "r"(a[1]), "r"(a[2]), "r"(a[3]), "r"(b0), "r"(b1));
}
__device__ __forceinline__ uint4 ld_relaxed4(const void* p) {
    uint4 v; asm volatile("ld.relaxed.gpu.global.v4.u32 {%0,%1,%2,%3}, [%4];" : "=r"(v.x), "=r"(v.y), "=r"(v.z), "=r"(v.w) : "l"(p) : "memory"); return v;
}
__device__ __forceinline__ uint2 ld_relaxed2(const void* p) {
    uint2 v; asm volatile("ld.relaxed.gpu.global.v2.u32 {%0,%1}, [%2];" : "=r"(v.x), "=r"(v.y) : "l"(p) : "memory"); return v;
}
__device__ __forceinline__ uint32_t ld_relaxed1(const void* p) {
    uint32_t v; asm volatile("ld.relaxed.gpu.global.u32 %0, [%1];" : "=r"(v) : "l"(p) : "memory"); return v;
}
__device__ __forceinline__ void st_relaxed4(void* p, uint32_t a, uint32_t b, uint32_t c, uint32_t d) {
    asm volatile("st.relaxed.gpu.global.v4.u32 [%0], {%1,%2,%3,%4};" :: "l"(p), "r"(a), "r"(b), "r"(c), "r"(d) : "memory");
}
__device__ __forceinline__ void st_relaxed1(void* p, uint32_t a) {
    asm volatile("st.relaxed.gpu.global.u32 [%0], %1;" :: "l"(p), "r"(a) : "memory");
}
__device__ __forceinline__ void st_relaxed2(void* p, uint32_t a, uint32_t b) {
    asm volatile("st.relaxed.gpu.global.v2.u32 [%0], {%1,%2};" :: "l"(p), "r"(a), "r"(b) : "memory");
}
__device__ __forceinline__ uint4 lds128(uint32_t a) { uint4 v; asm volatile("ld.shared.v4.u32 {%0,%1,%2,%3}, [%4];" : "=r"(v.x), "=r"(v.y), "=r"(v.z), "=r"(v.w) : "r"(a) : "memory"); return v; }
__device__ __forceinline__ void bar_cons() { asm volatile("bar.sync 1, 128;" ::: "memory"); }
__device__ __forceinline__ void bar_comb() { asm volatile("bar.sync 2, 128;" ::: "memory"); }
__device__ __forceinline__ float bfr(float v) { return __bfloat162float(__float2bfloat16_rn(v)); }
__device__ __forceinline__ uint32_t pack_bf16(float lo, float hi) {
    uint32_t r; asm("cvt.rn.bf16x2.f32 %0, %1, %2;" : "=r"(r) : "f"(hi), "f"(lo)); return r;
}
__device__ __forceinline__ float ex2(float x) { float y; asm("ex2.approx.ftz.f32 %0, %1;" : "=f"(y) : "f"(x)); return y; }
__device__ __forceinline__ float silu_f(float v) { return __fdividef(v, 1.0f + __expf(-v)); }
__device__ __forceinline__ uint32_t tagf(float v, uint32_t tag) { return (__float_as_uint(v) & ~1u) | tag; }
__device__ __forceinline__ float untagf(uint32_t w) { return __uint_as_float(w & ~1u); }
__device__ __forceinline__ uint32_t bad4(const uint4& v, uint32_t tag) { return ((v.x ^ tag) | (v.y ^ tag) | (v.z ^ tag) | (v.w ^ tag)) & 1u; }
__device__ __forceinline__ uint32_t pack_tag(float lo, float hi, uint32_t tag) {
    uint32_t l = ((__float_as_uint(lo) + 0x10000u) >> 16) & 0xFFFEu;
    uint32_t h = pack_bf16(0.f, hi) & 0xFFFF0000u;
    return h | l | tag;
}

__device__ __forceinline__ int dyn_tile(int n) { return n + NPLAIN * NST; }

__device__ __forceinline__ uint32_t addr_w32(uint32_t base, int lane, int mt, int ks) {
    int mat = lane >> 3, row = ks * 16 + (mat >> 1) * 8 + (lane & 7), c = mt * 2 + (mat & 1);
    return base + row * 64 + ((c ^ ((row >> 1) & 3)) << 4);
}
__device__ __forceinline__ uint32_t addr_kv(uint32_t base, int key, int chunk) {
    return base + (chunk >> 3) * 8192 + key * 128 + (((chunk & 7) ^ (key & 7)) << 4);
}

template <int NKS>
__device__ __forceinline__ void proj32(float (&acc)[4], uint32_t wbase, uint32_t bar, uint32_t xn, int lane, int mt, int ks0) {
    uint32_t xb[NKS / 2][4];
    const uint32_t xa = xn + ((lane & 7) * XP + (lane >> 3) * 8 + ks0 * 16) * 2;
#pragma unroll
    for (int i = 0; i < NKS / 2; i++) ldsm4(xb[i], xa + i * 64);
    float a4[4][4];
#pragma unroll
    for (int i = 0; i < 4; i++) { a4[i][0] = a4[i][1] = a4[i][2] = a4[i][3] = 0.f; }
    const uint32_t wa = addr_w32(wbase, lane, mt, ks0);
    if (ks0 < 12) mbar_wait(bar, 0);
    mbar_wait(bar + 8, 0);
    if (ks0 + NKS > 24) mbar_wait(bar + 16, 0);
#pragma unroll
    for (int i = 0; i < NKS; i++) {
        uint32_t a[4];
        ldsm4t(a, wa + i * 1024);
        mma16816(a4[i & 3], a, xb[i >> 1][(i & 1) * 2], xb[i >> 1][(i & 1) * 2 + 1]);
    }
#pragma unroll
    for (int i = 0; i < 4; i++) acc[i] = (a4[0][i] + a4[1][i]) + (a4[2][i] + a4[3][i]);
}

__device__ __forceinline__ void put_frag(float* dst, const float (&acc)[4], int mt, int g, int t) {
    dst[(2 * t) * 36 + mt * 16 + g] = acc[0];
    dst[(2 * t + 1) * 36 + mt * 16 + g] = acc[1];
    dst[(2 * t) * 36 + mt * 16 + g + 8] = acc[2];
    dst[(2 * t + 1) * 36 + mt * 16 + g + 8] = acc[3];
}
__device__ __forceinline__ void put_tile(uint32_t* dst, uint32_t w0, uint32_t w1, uint32_t w2, uint32_t w3, bool upper) {
    st_relaxed1(dst, w0); st_relaxed1(dst + DM, w1);
    if (upper) { st_relaxed1(dst + 8, w2); st_relaxed1(dst + DM + 8, w3); }
}
__device__ __forceinline__ uint32_t* fp_slot(int unit, int warp, int g, int t) {
    return g_fp + ((unit / GRP) * NB + 2 * t) * DM + (unit % GRP) * 64 + warp * 16 + g;
}

template <bool LATE>
__device__ __forceinline__ void ffn_unit(uint32_t sb, uint32_t bufG, uint32_t bufU, uint32_t bufD, uint32_t barG, uint32_t barU,
                                         uint32_t barD, int unit, int warp, int lane, uint32_t tag) {
    const int g = lane >> 2, t = lane & 3;
    const int hf = warp >> 1, mt = warp & 1;
    float* gu = reinterpret_cast<float*>(__cvta_shared_to_generic(sb + SM_GU));
    float acc[4];
    if (LATE) { mbar_wait(barG, 0); proj32<18>(acc, bufU, barU, sb + SM_XN, lane, mt, hf * 18); }
    else proj32<36>(acc, hf ? bufU : bufG, hf ? barU : barG, sb + SM_XN, lane, mt, 0);
    put_frag(gu + hf * 288, acc, mt, g, t);
    bar_cons();
    if (warp < 2) {
        uint32_t hw[2];
#pragma unroll
        for (int j = 0; j < 2; j++) {
            const int f = g * 36 + warp * 16 + j * 8 + 2 * t;
            const float2 p0 = *reinterpret_cast<const float2*>(gu + f), p1 = *reinterpret_cast<const float2*>(gu + 288 + f);
            float2 gg = p0, uu = p1;
            if (LATE) { gg = *reinterpret_cast<const float2*>(gu + 576 + f); uu = make_float2(p0.x + p1.x, p0.y + p1.y); }
            hw[j] = pack_bf16(bfr(silu_f(bfr(gg.x))) * bfr(uu.x), bfr(silu_f(bfr(gg.y))) * bfr(uu.y));
        }
        st_relaxed4(g_h + (unit * 2 + warp) * 32 + lane, (hw[0] << 16) | tag, (hw[0] & 0xFFFF0000u) | tag, (hw[1] << 16) | tag, (hw[1] & 0xFFFF0000u) | tag);
    }
    {
        const uint4* src = g_h + (unit / GRP) * (2 * GRP * 32) + warp * 32 + lane;
        uint4 v[5];
        uint32_t pend = warp < 2 ? 0x1Fu : 0xFu;
        Spin sp;
        if (LATE) __nanosleep(HDELAY);
        while (true) {
#pragma unroll
            for (int i = 0; i < 5; i++)
                if (pend >> i & 1) v[i] = ld_relaxed4(src + i * 128);
#pragma unroll
            for (int i = 0; i < 5; i++)
                if ((pend >> i & 1) && !__any_sync(~0u, bad4(v[i], tag))) {
                    pend &= ~(1u << i);
                    asm volatile("st.shared.v2.u32 [%0], {%1, %2};" :: "r"(sb + SM_HB + ((i * 4 + warp) * 32 + lane) * 8),
                                 "r"(__byte_perm(v[i].x, v[i].y, 0x7632)), "r"(__byte_perm(v[i].z, v[i].w, 0x7632)) : "memory");
                }
            if (!pend) break;
            __nanosleep(30);
            sp.tick();
        }
    }
    mbar_wait(barD, 0); mbar_wait(barD + 8, 0); mbar_wait(barD + 16, 0);
    uint32_t a[2 * GRP][4];
    {
        const int m4 = lane >> 3, row = (m4 >> 1) * 8 + (lane & 7), c = warp * 2 + (m4 & 1);
        const uint32_t a0 = bufD + row * 128 + ((c ^ (lane & 7)) << 4);
#pragma unroll
        for (int ks = 0; ks < 2 * GRP; ks++) ldsm4t(a[ks], a0 + ks * 2048);
    }
    bar_cons();
    float c0[4] = {0.f, 0.f, 0.f, 0.f}, c1[4] = {0.f, 0.f, 0.f, 0.f}, c2[4] = {0.f, 0.f, 0.f, 0.f};
#pragma unroll
    for (int ks = 0; ks < 2 * GRP; ks++) {
        uint32_t h0, h1;
        asm volatile("ld.shared.v2.u32 {%0, %1}, [%2];" : "=r"(h0), "=r"(h1) : "r"(sb + SM_HB + (ks * 32 + lane) * 8) : "memory");
        mma16816(ks % 3 == 0 ? c0 : ks % 3 == 1 ? c1 : c2, a[ks], h0, h1);
    }
    put_tile(fp_slot(unit, warp, g, t), tagf(c0[0] + c1[0] + c2[0], tag), tagf(c0[1] + c1[1] + c2[1], tag),
             tagf(c0[2] + c1[2] + c2[2], tag), tagf(c0[3] + c1[3] + c2[3], tag), true);
}

__device__ __forceinline__ void gather16(const uint32_t* base, float* red, int tid, uint32_t tag) {
    const int f = tid & 7;
    const uint32_t* src = base + (tid >> 3) * (NB * DM) + f * 4;
    uint4 v0, v1 = make_uint4(tag, tag, tag, tag);
    Spin sp;
    while (true) {
        v0 = ld_relaxed4(src);
        if (f == 0) v1 = ld_relaxed4(src + 32);
        if (!__any_sync(~0u, bad4(v0, tag) | bad4(v1, tag))) break;
        __nanosleep(30);
        sp.tick();
    }
    float a[8] = {untagf(v0.x), untagf(v0.y), untagf(v0.z), untagf(v0.w), untagf(v1.x), untagf(v1.y), untagf(v1.z), untagf(v1.w)};
#pragma unroll
    for (int i = 0; i < 8; i++) { a[i] += __shfl_xor_sync(~0u, a[i], 8); a[i] += __shfl_xor_sync(~0u, a[i], 16); }
    if ((tid & 31) < 8) {
        float* r = red + (tid >> 5) * 36;
        *reinterpret_cast<float4*>(r + f * 4) = make_float4(a[0], a[1], a[2], a[3]);
        if (f == 0) *reinterpret_cast<float4*>(r + 32) = make_float4(a[4], a[5], a[6], a[7]);
    }
}

__device__ __forceinline__ void finish(uint8_t* sg, __nv_bfloat16* out, int lane) {
    const float* red = reinterpret_cast<const float*>(sg + SM_RED);
    __syncwarp();
    uint32_t n = 0;
    if (lane == 0) asm volatile("atom.acq_rel.cta.shared.add.u32 %0, [%1], 1;" : "=r"(n) : "r"(s2u(sg + SM_DESC + 40)) : "memory");
    if (__shfl_sync(~0u, n, 0) != 7) return;
    __syncwarp();
    if (lane < 18) {
        float r[2];
#pragma unroll
        for (int i = 0; i < 2; i++) {
            const int c = lane * 2 + i;
            const float f = (red[c] + red[36 + c]) + (red[72 + c] + red[108 + c]);
            const float s = bfr((red[144 + c] + red[180 + c]) + (red[216 + c] + red[252 + c]));
            r[i] = red[288 + c] + bfr(s * bfr(silu_f(bfr(f))));
        }
        reinterpret_cast<uint32_t*>(out)[lane] = pack_bf16(r[0], r[1]);
    }
}

__global__ void __launch_bounds__(NTHREADS, 1)
fused_decode_kernel(const __grid_constant__ Maps maps, const __nv_bfloat16* __restrict__ x, __nv_bfloat16* __restrict__ out) {
    extern __shared__ uint8_t smem_raw[];
    const uint32_t sb = (s2u(smem_raw) + 1023u) & ~1023u;
    uint8_t* sg = smem_raw + (sb - s2u(smem_raw));
    const int tid = threadIdx.x, warp = tid >> 5, lane = tid & 31, cta = blockIdx.x;
    const uint32_t bar_full = sb + SM_BAR, bar_empty = bar_full + NST * 8;
    const uint32_t bar_q = bar_empty + NST * 8, bar_v = bar_q + NST * 8;
    const uint32_t bar_wq = bar_v + NST * 8, bar_wg = bar_wq + 24;
    const uint32_t bar_e = bar_wg + 24;
    const uint32_t bar_lu = bar_e + 72, bar_ld = bar_lu + 24, bar_wo = bar_ld + 24;
    const uint32_t bar_first = bar_wo + 32, bar_wfree = bar_first + 8, bar_gdone = bar_wfree + 8;
    volatile int* desc = reinterpret_cast<volatile int*>(sg + SM_DESC);

    uint32_t xr[2][9];
    if (warp < NST) {
#pragma unroll
        for (int r = 0; r < 2; r++)
#pragma unroll
            for (int i = 0; i < 9; i++)
                asm volatile("ld.global.nc.u32 %0, [%1];" : "=r"(xr[r][i]) : "l"(reinterpret_cast<const uint32_t*>(x + (warp * 2 + r) * DM) + i * 32 + lane));
    }
    if (tid >= 160 && tid < 167) asm volatile("prefetch.tensormap [%0];" :: "l"(reinterpret_cast<const CUtensorMap*>(&maps) + (tid - 160)) : "memory");
    uint32_t epoch = 0;
    if (warp != NST) epoch = ld_relaxed1(&g_state[1]);
    if (tid == NST * 32) {
        mbar_init(bar_wq, 1); mbar_init(bar_wq + 8, 1); mbar_init(bar_wq + 16, 1); mbar_init(bar_full, 1); mbar_init(bar_e, 1);
        asm volatile("fence.mbarrier_init.release.cluster;" ::: "memory");
        if (cta < 128) {
#pragma unroll
            for (int i = 0; i < 3; i++) { mbar_expect(bar_wq + i * 8, 12288); tma2d(sb + SM_WBUF + i * 12288, &maps.wq, cta * 32, i * 192, bar_wq + i * 8); }
        }
        if (cta >= NPLAIN) { mbar_expect(bar_e, 12288); tma2d(sb, &maps.wg, (NLATE + cta - NPLAIN) * 32, 0, bar_e); }
        else {
            uint64_t pol; asm volatile("createpolicy.fractional.L2::evict_first.b64 %0, 1.0;" : "=l"(pol));
            mbar_expect(bar_full, 16384);
            tma3d(sb, &maps.k, 0, cta * TILE, 0, bar_full, pol);
        }
    }

    if (warp == NST) {
        uint64_t pol; asm volatile("createpolicy.fractional.L2::evict_first.b64 %0, 1.0;" : "=l"(pol));
        constexpr int FN = 4, F0 = FN - INFLIGHT;
        uint32_t fifo[FN];
#pragma unroll
        for (int i = 0; i < FN; i++) fifo[i] = 0;
        auto gate = [&](int n) { for (int i = F0; i < F0 + n; i++) if (fifo[i]) mbar_wait(fifo[i] & ~1u, fifo[i] & 1u); };
        auto push = [&](uint32_t bar, uint32_t par) {
#pragma unroll
            for (int i = 0; i + 1 < FN; i++) fifo[i] = fifo[i + 1];
            fifo[FN - 1] = bar | par;
        };
        auto issue_half = [&](const CUtensorMap* m, int tile, uint32_t dst, uint32_t bar, uint32_t par) {
            mbar_expect(bar, 16384);
            tma3d(dst, m, 0, tile * TILE, 0, bar, pol);
            push(bar, par);
        };
        auto issue_k = [&](int tile, int st, uint32_t par) { desc[st] = tile; issue_half(&maps.k, tile, sb + st * STAGE, bar_full + st * 8, par); };
        auto issue_v = [&](int tile, int st, uint32_t par) { issue_half(&maps.v, tile, sb + st * STAGE + 16384, bar_v + st * 8, par); };
        auto piece = [&](const CUtensorMap* m, int c0, int c1, uint32_t dst, uint32_t bar, uint32_t bytes) {
            mbar_expect(bar, bytes);
            tma2d(dst, m, c0, c1, bar);
            push(bar, 0);
        };
        auto col_piece = [&](const CUtensorMap* m, int unit, int i, uint32_t buf, uint32_t bar) { piece(m, unit * 32, i * 192, buf + i * 12288, bar + i * 8, 12288); };
        auto down_piece = [&](int unit, int i, uint32_t buf, uint32_t bar) {
            piece(&maps.wd, (unit % GRP) * 64, (unit / GRP) * (GRP * 32) + i * 96, buf + i * 12288, bar + i * 8, 12288);
        };
        auto gate4 = [&]() { const uint32_t f = fifo[FN - SPIECES]; if (f) mbar_wait(f & ~1u, f & 1u); };
        const bool early = cta >= NPLAIN;
        const int eunit = NLATE + cta - NPLAIN;
        int next = 0;
        auto claim = [&]() { return (int)atomicAdd(&g_queue[0], 1u); };
        if (lane == 0) {
            if (cta < 128) for (int i = 0; i < 3; i++) push(bar_wq + i * 8, 0);
            push(early ? bar_e : bar_full, 0);
            next = claim();
            desc[0] = cta; desc[9] = 0; desc[10] = 0;
#pragma unroll
            for (int i = 1; i < NBAR; i++) {
                const int o = i * 8;
                if (o >= 4 * NST * 8 && o < 4 * NST * 8 + 24) continue;
                if (o == 4 * NST * 8 + 48) continue;
                mbar_init(bar_full + o, bar_full + o == bar_gdone ? 2 : 1);
            }
            asm volatile("fence.mbarrier_init.release.cluster;" ::: "memory");
        }
        __syncwarp();
        asm volatile("bar.arrive 3, %0;" :: "n"(NTHREADS) : "memory");
        if (lane == 0) {
            if (early) {
                for (int i = 1; i < 3; i++) { gate4(); col_piece(&maps.wg, eunit, i, sb, bar_e); }
                for (int i = 0; i < 3; i++) { gate4(); col_piece(&maps.wu, eunit, i, sb + STAGE, bar_e + 24); }
                for (int i = 0; i < 3; i++) { gate4(); down_piece(eunit, i, sb + 2 * STAGE, bar_e + 48); }
                const int tile = dyn_tile(next);
                gate4(); issue_k(tile, 3, 0); mbar_arrive(bar_first);
                next = claim();
                gate4(); issue_v(tile, 3, 0);
            } else {
                gate4(); issue_v(cta, 0, 0);
#pragma unroll
                for (int i = 1; i < NST; i++) { gate4(); issue_k(cta + i * NPLAIN, i, 0); gate4(); issue_v(cta + i * NPLAIN, i, 0); }
            }
            if (cta < 128) mbar_wait(bar_wfree, 0);
            if (cta < NLATE) for (int i = 0; i < 3; i++) { gate4(); col_piece(&maps.wg, cta, i, sb + SM_WBUF, bar_wg); }
            if (early) mbar_wait(bar_q + 24, 0);
            int st = 0; uint32_t ph = 0;
            while (true) {
                if (next < 0) {
                    Spin sp;
                    while (!mbar_test(fifo[F0] & ~1u, fifo[F0] & 1u)) {
                        if (desc[9] >= NDYN - PEEK && ld_relaxed1(&g_queue[0]) >= (unsigned)NDYN) { next = NDYN; break; }
                        __nanosleep(100);
                        sp.tick();
                    }
                    if (next >= NDYN) break;
                    mbar_wait(bar_empty + st * 8, ph);
                    next = claim();
                } else {
                    gate(1);
                    mbar_wait(bar_empty + st * 8, ph);
                }
                if (next >= NDYN) break;
                const int tile = dyn_tile(next);
                const uint32_t par = (early && st < 3) ? ph : ph ^ 1u;
                issue_k(tile, st, par);
                desc[9] = next;
                mbar_expect(bar_q + st * 8, 1024);
                bulk_g2s(sb + st * STAGE + 32768, g_q + (tile / TPP) * 256, 1024, bar_q + st * 8);
                next = next >= NDYN - LATECLAIM ? -1 : claim();
                if (next >= 0) gate(1);
                issue_v(tile, st, par);
                if (++st == NST) { st = 0; ph ^= 1; }
            }
            desc[9] = NDYN;
            const int stU = st;
            desc[4] = stU;
#pragma unroll
            for (int i = 0; i < F0; i++) fifo[i] = 0;
            int ends = 0, k = cta < NLATE ? 0 : 6;
            const int kend = cta < 128 ? 10 : 6;
            if (cta < NLATE) mbar_wait(bar_gdone, 0);
            Spin sp;
            while (ends < NST || k < kend) {
                if (ends < NST && mbar_test(bar_empty + st * 8, ph)) {
#pragma unroll
                    for (int i = 0; i < FN; i++) if ((fifo[i] & ~1u) == bar_full + st * 8) fifo[i] = 0;
                    desc[st] = -1;
                    mbar_arrive(bar_full + st * 8);
                    if (++st == NST) { st = 0; ph ^= 1; }
                    ends++;
                }
                const uint32_t f = fifo[FN - EPIECES];
                if (k < kend && ends >= (k < 3 ? 1 : k < 6 ? 2 : 0) && (f == 0 || mbar_test(f & ~1u, f & 1u))) {
                    if (k < 3) col_piece(&maps.wu, cta, k, sb + stU * STAGE, bar_lu);
                    else if (k < 6) down_piece(cta, k - 3, sb + ((stU + 1) % NST) * STAGE, bar_ld);
                    else piece(&maps.wo, (cta & 7) * 72, (cta >> 3) * 256 + (k - 6) * 64, sb + SM_WBUF + (k - 6) * 9216, bar_wo + (k - 6) * 8, 9216);
                    k++;
                }
                sp.tick();
            }
            if (atomicAdd(&g_state[0], 1u) == NCTA - 1) {
                g_queue[0] = 0; g_state[0] = 0;
                g_state[1] = g_state[1] + 1;
            }
        }
    } else if (warp < NST) {
        const int g = lane >> 2, t = lane & 3;
        if (tid < 36 && cta < 128)
            reinterpret_cast<float*>(sg + SM_RED)[288 + tid] = __bfloat162float(x[cta * 36 + tid]);
        {
#pragma unroll
            for (int r = 0; r < 2; r++) {
                float v[18], s = 0.f;
#pragma unroll
                for (int i = 0; i < 9; i++) { v[2 * i] = __uint_as_float(xr[r][i] << 16); v[2 * i + 1] = __uint_as_float(xr[r][i] & 0xFFFF0000u); s += v[2 * i] + v[2 * i + 1]; }
#pragma unroll
                for (int o = 16; o; o >>= 1) s += __shfl_xor_sync(~0u, s, o);
                const float mean = s * (1.0f / DM);
                float q = 0.f;
#pragma unroll
                for (int i = 0; i < 18; i++) { float d = v[i] - mean; q += d * d; }
#pragma unroll
                for (int o = 16; o; o >>= 1) q += __shfl_xor_sync(~0u, q, o);
                const float mb = bfr(mean), rden = __frcp_rn(bfr(__fsqrt_rn(bfr(bfr(q * (1.0f / DM)) + 1e-5f))));
                uint32_t* xn = reinterpret_cast<uint32_t*>(sg + SM_XN) + (warp * 2 + r) * (XP / 2);
#pragma unroll
                for (int i = 0; i < 9; i++) xn[i * 32 + lane] = pack_bf16(bfr(v[2 * i] - mb) * rden, bfr(v[2 * i + 1] - mb) * rden);
            }
        }
        const uint32_t tag = (epoch & 1u) ^ 1u;
        asm volatile("bar.sync 3, %0;" :: "n"(NTHREADS), "r"(tag) : "memory");
        if (cta < 128) {
            float acc[4];
            const int mt = warp & 1, kh = warp >> 1;
            proj32<18>(acc, sb + SM_WBUF, bar_wq, sb + SM_XN, lane, mt, kh * 18);
            float* gu = reinterpret_cast<float*>(sg + SM_GU);
            put_frag(gu + kh * 288, acc, mt, g, t);
            bar_cons();
            {
                const int b = tid >> 4, c = (tid & 15) * 2;
                const float q0 = gu[b * 36 + c] + gu[(8 + b) * 36 + c], q1 = gu[b * 36 + c + 1] + gu[(8 + b) * 36 + c + 1];
                const int hq = cta >> 2, d = (cta & 3) * 32 + c;
                const int off = (b * HKV + (hq >> 1)) * 256 + (hq & 1) * 128 + (d >> 4) * 16 + ((d & 7) >> 1) * 4 + ((d >> 3) & 1) * 2;
                const uint32_t pk = pack_bf16(q0, q1);
                st_relaxed2(g_q + off, (pk << 16) | tag, (pk & 0xFFFF0000u) | tag);
            }
            bar_cons();
            if (tid == 0) mbar_arrive(bar_wfree);
        }
        if (cta >= NPLAIN) {
            ffn_unit<false>(sb, sb, sb + STAGE, sb + 2 * STAGE, bar_e, bar_e + 24, bar_e + 48, NLATE + cta - NPLAIN, warp, lane, tag);
            bar_cons();
            if (warp < 3 && lane == 0) mbar_arrive(bar_empty + warp * 8);
        }
        const uint32_t kb = sb + warp * STAGE, vb = kb + 16384, qb = kb + 32768;
        const int mat = lane >> 3, r8 = lane & 7;
        const int kkey = (mat & 1) ? 8 + ((r8 + 4) & 7) : r8;
        const int rho = (r8 >> 1) + (mat >> 1) * 4;
        const int vkey = (r8 & 1) ? 8 + ((rho + 4) & 7) : rho;
        const float sc = 1.4426950408889634f;
        uint32_t ph = 0;
        while (true) {
            mbar_wait(bar_full + warp * 8, ph);
            ph ^= 1;
            const int tile = desc[warp];
            if (tile < 0) break;
            mbar_wait(bar_q + warp * 8, ph ^ 1u);
            uint32_t qf[16];
            {
                const bool on = (g == 0) || (g == 2);
                uint4 v[8];
                uint32_t bad = 0;
#pragma unroll
                for (int j = 0; j < 8; j++) {
                    v[j] = make_uint4(tag, tag, tag, tag);
                    if (on) v[j] = lds128(qb + (g >> 1) * 512 + j * 64 + t * 16);
                    bad |= (v[j].x ^ tag) | (v[j].y ^ tag) | (v[j].z ^ tag) | (v[j].w ^ tag);
                }
                if (__any_sync(~0u, bad & 1u)) {
                    Spin sp;
                    do {
                        bad = 0;
                        if (on) {
#pragma unroll
                            for (int j = 0; j < 8; j++) v[j] = ld_relaxed4(g_q + (tile / TPP) * 256 + (g >> 1) * 128 + j * 16 + t * 4);
#pragma unroll
                            for (int j = 0; j < 8; j++) bad |= bad4(v[j], tag);
                        }
                        sp.tick();
                    } while (__any_sync(~0u, bad));
                }
#pragma unroll
                for (int j = 0; j < 8; j++) { qf[2 * j] = __byte_perm(v[j].x, v[j].y, 0x7632); qf[2 * j + 1] = __byte_perm(v[j].z, v[j].w, 0x7632); }
            }
            float s[4][4];
#pragma unroll
            for (int mt = 0; mt < 4; mt++) { s[mt][0] = s[mt][1] = s[mt][2] = s[mt][3] = 0.f; }
#pragma unroll
            for (int ks = 0; ks < 8; ks++)
#pragma unroll
                for (int mt = 0; mt < 4; mt++) {
                    uint32_t a[4];
                    ldsm4(a, addr_kv(kb, mt * 16 + kkey, 2 * ks + (mat >> 1)));
                    mma16816(s[mt], a, qf[2 * ks], qf[2 * ks + 1]);
                }
#pragma unroll
            for (int mt = 0; mt < 4; mt++) {
                const uint32_t r1 = pack_bf16(s[mt][0], s[mt][2]);
                const uint32_t r2 = pack_bf16(__uint_as_float(r1 << 16) * 0.08838834764831845f, __uint_as_float(r1 & 0xFFFF0000u) * 0.08838834764831845f);
                s[mt][0] = __uint_as_float(r2 << 16); s[mt][2] = __uint_as_float(r2 & 0xFFFF0000u);
            }
            float m = fmaxf(fmaxf(fmaxf(s[0][0], s[0][2]), fmaxf(s[1][0], s[1][2])), fmaxf(fmaxf(s[2][0], s[2][2]), fmaxf(s[3][0], s[3][2])));
            m = fmaxf(m, __shfl_xor_sync(~0u, m, 4));
            m = fmaxf(m, __shfl_xor_sync(~0u, m, 8));
            m = fmaxf(m, __shfl_xor_sync(~0u, m, 16));
            const float ms = untagf(__float_as_uint(m * sc));
            float l = 0.f;
            uint32_t pb[4][2];
#pragma unroll
            for (int mt = 0; mt < 4; mt++) {
                const float p0 = ex2(fmaf(s[mt][0], sc, -ms)), p1 = ex2(fmaf(s[mt][2], sc, -ms));
                l += p0 + p1;
                const uint32_t pk = pack_bf16(p0, p1);
                pb[mt][0] = __shfl_sync(~0u, pk, 4 * t + (g & 1));
                pb[mt][1] = __shfl_sync(~0u, pk, 4 * (t + 4) + (g & 1));
            }
            l += __shfl_xor_sync(~0u, l, 4);
            l += __shfl_xor_sync(~0u, l, 8);
            l += __shfl_xor_sync(~0u, l, 16);
            float o[8][4];
#pragma unroll
            for (int i = 0; i < 8; i++) { o[i][0] = o[i][1] = o[i][2] = o[i][3] = 0.f; }
            mbar_wait(bar_v + warp * 8, ph ^ 1u);
#pragma unroll
            for (int kk = 0; kk < 4; kk++)
#pragma unroll
                for (int i = 0; i < 8; i++) {
                    uint32_t a[4];
                    ldsm4t(a, addr_kv(vb, kk * 16 + vkey, 2 * i + (mat & 1)));
                    mma16816(o[i], a, pb[kk][0], pb[kk][1]);
                }
            __syncwarp();
            if (lane == 0) mbar_arrive(bar_empty + warp * 8);
            const float inv = __fdividef(1.0f, l);
            const float inv1 = __shfl_down_sync(~0u, inv, 1);
            const int pair = tile / TPP, tt = tile % TPP;
            if (t == 0) {
                uint2* dst = g_po + ((size_t)pair * 8 * TPP + tt) * 8 + g;
#pragma unroll
                for (int qd = 0; qd < 4; qd++) {
                    st_relaxed2(dst + (size_t)qd * TPP * 8,
                                pack_tag(o[2 * qd][0] * inv, o[2 * qd][2] * inv, tag), pack_tag(o[2 * qd + 1][0] * inv, o[2 * qd + 1][2] * inv, tag));
                    st_relaxed2(dst + (size_t)(4 + qd) * TPP * 8,
                                pack_tag(o[2 * qd][1] * inv1, o[2 * qd][3] * inv1, tag), pack_tag(o[2 * qd + 1][1] * inv1, o[2 * qd + 1][3] * inv1, tag));
                }
            }
            {
                const uint32_t m_ = tagf(ms, tag), l_ = tagf(l, tag);
                const uint32_t m0 = __shfl_sync(~0u, m_, 0), l0 = __shfl_sync(~0u, l_, 0), m1 = __shfl_sync(~0u, m_, 1), l1 = __shfl_sync(~0u, l_, 1);
                if (lane < 2) st_relaxed4(g_ml + tile * 2 + lane, m0, l0, m1, l1);
            }
        }
        if (cta < NLATE) {
            {
                const uint32_t inv = tag ^ 1u;
                put_tile(fp_slot(cta, warp, g, t), inv, inv, inv, inv, true);
                if (warp < 2) st_relaxed4(g_h + (cta * 2 + warp) * 32 + lane, inv, inv, inv, inv);
            }
            const int stU = desc[4];
            ffn_unit<true>(sb, 0, sb + stU * STAGE, sb + ((stU + 1) % NST) * STAGE, bar_gdone, bar_lu, bar_ld, cta, warp, lane, tag);
        }
        if (cta < 128) {
            gather16(g_fp + cta * 36, reinterpret_cast<float*>(sg + SM_RED), tid, tag);
            finish(sg, out + cta * 36, lane);
        }
    } else {
        const int cw = warp - NST - 1, ctid = tid - (NST + 1) * 32;
        const uint32_t tag = (epoch & 1u) ^ 1u;
        {
            const bool early = cta >= NPLAIN;
            asm volatile("bar.sync 3, %0;" :: "n"(NTHREADS), "r"(tag) : "memory");
            if (!early || cw == 3) {
                int tile = cta + cw * NPLAIN;
                if (early) {
                    mbar_wait(bar_first, 0);
                    tile = desc[3];
                } else {
                    mbar_wait(bar_wfree, 0);
                    __nanosleep(QDELAY);
                }
                const uint32_t* src = g_q + (tile / TPP) * 256 + lane * 4;
                uint4 v0, v1;
                Spin sp;
                while (true) {
                    v0 = ld_relaxed4(src); v1 = ld_relaxed4(src + 128);
                    if (!__any_sync(~0u, bad4(v0, tag) | bad4(v1, tag))) break;
                    __nanosleep(200);
                    sp.tick();
                }
                uint4* dst = reinterpret_cast<uint4*>(sg + cw * STAGE + 32768) + lane;
                dst[0] = v0; dst[32] = v1;
                __syncwarp();
                if (lane == 0) mbar_arrive(bar_q + cw * 8);
            }
            if (cw < 2 && cta < NLATE) {
                float acc[4];
                proj32<36>(acc, sb + SM_WBUF, bar_wg, sb + SM_XN, lane, cw, 0);
                put_frag(reinterpret_cast<float*>(sg + SM_GL), acc, cw, lane >> 2, lane & 3);
                __syncwarp();
                if (lane == 0) mbar_arrive(bar_gdone);
            }
        }
        if (cta < 128) {
            const int g = lane >> 2, t = lane & 3;
            const int hkv = cta >> 3, head = (cta >> 2) & 1, qd = cta & 3;
            uint32_t* sdst = g_sp + (hkv * NB + 2 * t) * DM + (cta & 7) * 72 + cw * 16 + g;
            const uint4* oxs = g_ox + (hkv * 8 * NB + g) * 8 + t;
            uint32_t ob[16][2];
            auto collect_o = [&](bool on) {
                uint4 v[16];
                Spin sp;
                while (true) {
                    uint32_t bad = 0;
                    if (on) {
#pragma unroll
                        for (int i = 0; i < 16; i++) v[i] = ld_relaxed4(oxs + (i >> 1) * (NB * 8) + (i & 1) * 4);
#pragma unroll
                        for (int i = 0; i < 16; i++) bad |= bad4(v[i], tag);
                    }
                    if (!__any_sync(~0u, bad)) break;
                    __nanosleep(30);
                    sp.tick();
                }
                if (on) {
#pragma unroll
                    for (int i = 0; i < 16; i++) { ob[i][0] = __byte_perm(v[i].x, v[i].y, 0x7632); ob[i][1] = __byte_perm(v[i].z, v[i].w, 0x7632); }
                }
            };
#pragma unroll 1
            for (int b = 0; b < NB; b++) {
                const int p = b * HKV + hkv;
                uint2 e;
                uint4 v[4];
                const uint2* rows = g_po + ((size_t)((p * 2 + head) * 4 + qd) * TPP + cw * 32 + g) * 8 + t * 2;
                {
                    const uint2* mlp = reinterpret_cast<const uint2*>(g_ml + (p * TPP + cw * 32 + lane) * 2) + head;
                    Spin sp;
                    const int plast = (p + 1) * TPP - NPLAIN * NST;
                    const int target = min(plast + MARGIN, NDYN - TAILPOLL);
                    while (desc[9] < target) { __nanosleep(250); sp.tick(); }
                    if (b == NB - 1) collect_o(g < NB - 1);
                    while (true) {
                        e = ld_relaxed2(mlp);
                        const uint32_t miss = __ballot_sync(~0u, ((e.x ^ tag) | (e.y ^ tag)) & 1u);
                        if (!miss) break;
                        __nanosleep(miss == ~0u ? 300 : 20);
                        sp.tick();
                    }
                }
#pragma unroll
                for (int i = 0; i < 4; i++) v[i] = ld_relaxed4(rows + i * 64);
                const float m = untagf(e.x);
                float M = m;
#pragma unroll
                for (int o = 16; o; o >>= 1) M = fmaxf(M, __shfl_xor_sync(~0u, M, o));
                const float w = ex2(m - M) * untagf(e.y);
                float L = w;
#pragma unroll
                for (int o = 16; o; o >>= 1) L += __shfl_xor_sync(~0u, L, o);
                float wr[4];
#pragma unroll
                for (int i = 0; i < 4; i++) wr[i] = __shfl_sync(~0u, w, i * 8 + g);
                {
                    Spin sp;
                    while (__any_sync(~0u, bad4(v[0], tag) | bad4(v[1], tag) | bad4(v[2], tag) | bad4(v[3], tag))) {
#pragma unroll
                        for (int i = 0; i < 4; i++) v[i] = ld_relaxed4(rows + i * 64);
                        sp.tick();
                    }
                }
                float acc[8];
#pragma unroll
                for (int k = 0; k < 8; k++) acc[k] = 0.f;
#pragma unroll
                for (int i = 0; i < 4; i++) {
                    const uint32_t u[4] = {v[i].x, v[i].y, v[i].z, v[i].w};
#pragma unroll
                    for (int k = 0; k < 4; k++) {
                        acc[2 * k] = fmaf(wr[i], __uint_as_float((u[k] << 16) & 0xFFFE0000u), acc[2 * k]);
                        acc[2 * k + 1] = fmaf(wr[i], __uint_as_float(u[k] & 0xFFFF0000u), acc[2 * k + 1]);
                    }
                }
#pragma unroll
                for (int k = 0; k < 8; k++) {
                    acc[k] += __shfl_xor_sync(~0u, acc[k], 4);
                    acc[k] += __shfl_xor_sync(~0u, acc[k], 8);
                    acc[k] += __shfl_xor_sync(~0u, acc[k], 16);
                }
                float* part = reinterpret_cast<float*>(sg + SM_PART) + (b & 1) * 160;
                if (g == 0) {
#pragma unroll
                    for (int k = 0; k < 4; k++) *reinterpret_cast<float2*>(part + cw * 40 + k * 8 + 2 * t) = make_float2(acc[k], acc[k + 4]);
                    if (t == 0) *reinterpret_cast<float2*>(part + cw * 40 + 32) = make_float2(M, L);
                }
                bar_comb();
                if (ctid < 8) {
                    float2 ml4[4];
#pragma unroll
                    for (int i = 0; i < 4; i++) ml4[i] = *reinterpret_cast<const float2*>(part + i * 40 + 32);
                    const float MM = fmaxf(fmaxf(ml4[0].x, ml4[1].x), fmaxf(ml4[2].x, ml4[3].x));
                    float sw[4], LL = 0.f;
#pragma unroll
                    for (int i = 0; i < 4; i++) { sw[i] = ex2(ml4[i].x - MM); LL = fmaf(sw[i], ml4[i].y, LL); }
                    const float inv = 1.0f / LL;
                    uint32_t pk[2];
#pragma unroll
                    for (int j = 0; j < 2; j++) {
                        float o0 = 0.f, o1 = 0.f;
#pragma unroll
                        for (int i = 0; i < 4; i++) {
                            const float2 pv = *reinterpret_cast<const float2*>(part + i * 40 + g * 16 + j * 8 + 2 * t);
                            o0 = fmaf(sw[i], pv.x, o0); o1 = fmaf(sw[i], pv.y, o1);
                        }
                        pk[j] = pack_bf16(o0 * inv, o1 * inv);
                    }
                    uint4* dst = g_ox + (cta * NB + b) * 8 + ctid;
                    st_relaxed4(dst, (pk[0] << 16) | tag, (pk[0] & 0xFFFF0000u) | tag, (pk[1] << 16) | tag, (pk[1] & 0xFFFF0000u) | tag);
                    if (b == NB - 2) st_relaxed4(dst + 8, tag ^ 1u, tag ^ 1u, tag ^ 1u, tag ^ 1u);
                }
                if (b == NB - 2) {
                    const uint32_t inv = tag ^ 1u;
                    put_tile(sdst, inv, inv, inv, inv, true);
                    if (cw == 0) put_tile(sdst + 64, inv, inv, inv, inv, false);
                }
                __syncwarp();
            }
            {
                __nanosleep(ODELAY);
                const int m4 = lane >> 3;
                const uint32_t a0 = sb + SM_WBUF + ((m4 >> 1) * 8 + (lane & 7)) * 144 + (m4 & 1) * 16;
                uint32_t a[16][4], a2[4][4];
                auto load_a = [&]() {
#pragma unroll
                    for (int ks = 0; ks < 16; ks++) ldsm4t(a[ks], a0 + ks * (16 * 144) + cw * 32);
#pragma unroll
                    for (int i = 0; i < 4; i++) ldsm4t(a2[i], a0 + (cw * 4 + i) * (16 * 144) + 128);
                };
                bool have_a = false;
                const uint4* src = g_ox + ((hkv * 8 + (lane >> 3)) * NB + NB - 1) * 8 + (lane & 7);
                uint4 v0, v1;
                Spin sp;
                while (true) {
                    v0 = ld_relaxed4(src); v1 = ld_relaxed4(src + 4 * NB * 8);
                    if (!have_a && __all_sync(~0u, mbar_test(bar_wo + (lane & 3) * 8, 0))) { __syncwarp(); load_a(); have_a = true; }
                    if (!__any_sync(~0u, bad4(v0, tag) | bad4(v1, tag))) break;
                    sp.tick();
                }
                {
                    uint4* ox = reinterpret_cast<uint4*>(sg + SM_OB) + cw * 32;
                    ox[(lane & 3) * 8 + (lane >> 2)] = make_uint4(__byte_perm(v0.x, v0.y, 0x7632), __byte_perm(v0.z, v0.w, 0x7632),
                                                                  __byte_perm(v1.x, v1.y, 0x7632), __byte_perm(v1.z, v1.w, 0x7632));
                    __syncwarp();
                    if (g == NB - 1) {
#pragma unroll
                        for (int i = 0; i < 8; i++) { const uint4 w4 = ox[t * 8 + i]; ob[i][0] = w4.x; ob[i][1] = w4.y; ob[8 + i][0] = w4.z; ob[8 + i][1] = w4.w; }
                    }
                }
                float c0[4] = {0.f, 0.f, 0.f, 0.f}, c1[4] = {0.f, 0.f, 0.f, 0.f}, c2[4] = {0.f, 0.f, 0.f, 0.f};
                uint32_t b2[4][2];
#pragma unroll
                for (int i = 0; i < 4; i++) {
                    b2[i][0] = cw == 0 ? ob[i][0] : cw == 1 ? ob[4 + i][0] : cw == 2 ? ob[8 + i][0] : ob[12 + i][0];
                    b2[i][1] = cw == 0 ? ob[i][1] : cw == 1 ? ob[4 + i][1] : cw == 2 ? ob[8 + i][1] : ob[12 + i][1];
                }
                if (have_a) {
#pragma unroll
                    for (int i = 0; i < 4; i++) mma16816(c2, a2[i], b2[i][0], b2[i][1]);
#pragma unroll
                    for (int ks = 0; ks < 16; ks++) mma16816((ks & 1) ? c1 : c0, a[ks], ob[ks][0], ob[ks][1]);
                } else {
#pragma unroll
                    for (int pc = 0; pc < 4; pc++) {
                        mbar_wait(bar_wo + pc * 8, 0);
#pragma unroll
                        for (int i = 0; i < 4; i++) ldsm4t(a[i], a0 + (pc * 4 + i) * (16 * 144) + cw * 32);
                        if (pc == cw) {
#pragma unroll
                            for (int i = 0; i < 4; i++) ldsm4t(a2[i], a0 + (pc * 4 + i) * (16 * 144) + 128);
#pragma unroll
                            for (int i = 0; i < 4; i++) mma16816(c2, a2[i], b2[i][0], b2[i][1]);
                        }
#pragma unroll
                        for (int i = 0; i < 4; i++) mma16816((i & 1) ? c1 : c0, a[i], ob[pc * 4 + i][0], ob[pc * 4 + i][1]);
                    }
                }
                float2* x4 = reinterpret_cast<float2*>(sg + SM_PART);
                x4[cw * 32 + lane] = make_float2(c2[0], c2[1]);
                put_tile(sdst, tagf(c0[0] + c1[0], tag), tagf(c0[1] + c1[1], tag), tagf(c0[2] + c1[2], tag), tagf(c0[3] + c1[3], tag), true);
                bar_comb();
                if (cw == 0) {
                    const float2 p0 = x4[lane], p1 = x4[32 + lane], p2 = x4[64 + lane], p3 = x4[96 + lane];
                    put_tile(sdst + 64, tagf((p0.x + p1.x) + (p2.x + p3.x), tag), tagf((p0.y + p1.y) + (p2.y + p3.y), tag), 0, 0, false);
                }
            }
            gather16(g_sp + cta * 36, reinterpret_cast<float*>(sg + SM_RED) + 144, ctid, tag);
            finish(sg, out + cta * 36, lane);
        }
    }
}

#define f_q (reinterpret_cast<float*>(g_po))
#define f_o (f_q + NB * 4096)
#define f_h (f_o + NB * 4096)

__global__ void fb_proj(const __nv_bfloat16* x, const __nv_bfloat16* wq, const __nv_bfloat16* wg, const __nv_bfloat16* wu) {
    __shared__ float xn[DM];
    const int b = blockIdx.y, n = blockIdx.x * blockDim.x + threadIdx.x;
    float s = 0.f, q = 0.f;
    for (int i = 0; i < DM; i++) s += __bfloat162float(x[b * DM + i]);
    const float mean = s / DM;
    for (int i = 0; i < DM; i++) { const float d = __bfloat162float(x[b * DM + i]) - mean; q += d * d; }
    const float den = bfr(sqrtf(bfr(bfr(q / DM) + 1e-5f)));
    for (int i = threadIdx.x; i < DM; i += blockDim.x) xn[i] = bfr(bfr(__bfloat162float(x[b * DM + i]) - bfr(mean)) / den);
    __syncthreads();
    if (n < 4096) {
        float a = 0.f;
        for (int k = 0; k < DM; k++) a += xn[k] * __bfloat162float(wq[(size_t)k * 4096 + n]);
        f_q[b * 4096 + n] = bfr(a);
    }
    if (n < FF) {
        float g = 0.f, u = 0.f;
        for (int k = 0; k < DM; k++) { g += xn[k] * __bfloat162float(wg[(size_t)k * FF + n]); u += xn[k] * __bfloat162float(wu[(size_t)k * FF + n]); }
        f_h[b * FF + n] = bfr(bfr(silu_f(bfr(g))) * bfr(u));
    }
}
__global__ void fb_attn(const __nv_bfloat16* K, const __nv_bfloat16* V) {
    __shared__ float sc[SK], red[128];
    const int t = threadIdx.x, b = blockIdx.x >> 5, h = blockIdx.x & 31;
    const __nv_bfloat16* k = K + (size_t)(b * HKV + (h >> 1)) * SK * 128;
    const __nv_bfloat16* v = V + (size_t)(b * HKV + (h >> 1)) * SK * 128;
    const float* q = f_q + b * 4096 + h * 128;
    float m = -INFINITY, l = 0.f, o = 0.f;
    for (int j = t; j < SK; j += 128) {
        float s = 0.f;
        for (int d = 0; d < 128; d++) s += q[d] * __bfloat162float(k[(size_t)j * 128 + d]);
        sc[j] = bfr(bfr(s) * 0.08838834764831845f); m = fmaxf(m, sc[j]);
    }
    red[t] = m; __syncthreads();
    for (int i = 0; i < 128; i++) m = fmaxf(m, red[i]);
    __syncthreads();
    for (int j = t; j < SK; j += 128) { sc[j] = __expf(sc[j] - m); l += sc[j]; }
    red[t] = l; __syncthreads();
    l = 0.f;
    for (int i = 0; i < 128; i++) l += red[i];
    for (int j = 0; j < SK; j++) o += sc[j] * __bfloat162float(v[(size_t)j * 128 + t]);
    f_o[b * 4096 + h * 128 + t] = bfr(o / l);
}
__global__ void fb_out(const __nv_bfloat16* x, const __nv_bfloat16* wo, const __nv_bfloat16* wd, __nv_bfloat16* out) {
    const int b = blockIdx.y, n = blockIdx.x * blockDim.x + threadIdx.x;
    float s = 0.f, f = 0.f;
    for (int k = 0; k < 4096; k++) s += f_o[b * 4096 + k] * __bfloat162float(wo[(size_t)k * DM + n]);
    for (int k = 0; k < FF; k++) f += f_h[b * FF + k] * __bfloat162float(wd[(size_t)k * DM + n]);
    out[b * DM + n] = __float2bfloat16_rn(__bfloat162float(x[b * DM + n]) + bfr(bfr(s) * bfr(silu_f(bfr(f)))));
}

typedef CUresult (*EncodeFn)(CUtensorMap*, CUtensorMapDataType, cuuint32_t, void*, const cuuint64_t*, const cuuint64_t*,
                             const cuuint32_t*, const cuuint32_t*, CUtensorMapInterleave, CUtensorMapSwizzle,
                             CUtensorMapL2promotion, CUtensorMapFloatOOBfill);

void make_map(EncodeFn enc, CUtensorMap* m, const void* p, int rank, const cuuint64_t* dims, const cuuint64_t* strides,
              const cuuint32_t* box, CUtensorMapSwizzle sw, CUtensorMapL2promotion promo) {
    cuuint32_t es[3] = {1, 1, 1};
    enc(m, CU_TENSOR_MAP_DATA_TYPE_BFLOAT16, rank, const_cast<void*>(p), dims, strides, box, es,
        CU_TENSOR_MAP_INTERLEAVE_NONE, sw, promo, CU_TENSOR_MAP_FLOAT_OOB_FILL_NONE);
}

}

extern "C" void kernel_launch(void* const* d_in, const int* in_sizes, int n_in, void* d_out, int out_size) {
    (void)in_sizes; (void)n_in; (void)out_size;
    static EncodeFn enc = nullptr;
    static int mode = 0;
    if (!mode) {
        void* fn = nullptr;
        cudaDriverEntryPointQueryResult qr;
        cudaGetDriverEntryPoint("cuTensorMapEncodeTiled", &fn, cudaEnableDefault, &qr);
        enc = (EncodeFn)fn;
        int dev = 0, sms = 0, occ = 0;
        cudaGetDevice(&dev);
        cudaDeviceGetAttribute(&sms, cudaDevAttrMultiProcessorCount, dev);
        cudaFuncSetAttribute(fused_decode_kernel, cudaFuncAttributeMaxDynamicSharedMemorySize, SMEM_BYTES);
        cudaOccupancyMaxActiveBlocksPerMultiprocessor(&occ, fused_decode_kernel, NTHREADS, SMEM_BYTES);
        mode = (enc && occ * sms >= NCTA) ? 1 : 2;
    }
    typedef const __nv_bfloat16* P;
    if (mode == 2) {
        fb_proj<<<dim3(FF / 128, NB), 128>>>((P)d_in[0], (P)d_in[3], (P)d_in[6], (P)d_in[7]);
        fb_attn<<<NB * 32, 128>>>((P)d_in[1], (P)d_in[2]);
        fb_out<<<dim3(DM / 64, NB), 64>>>((P)d_in[0], (P)d_in[4], (P)d_in[8], (__nv_bfloat16*)d_out);
        return;
    }
    Maps maps;
    const cuuint64_t kvrows = (cuuint64_t)NPAIR * SK;
    for (int i = 0; i < 2; i++) {
        cuuint64_t dims[3] = {64, kvrows, 2}, strides[2] = {256, 128};
        cuuint32_t box[3] = {64, TILE, 2};
        make_map(enc, i ? &maps.v : &maps.k, d_in[1 + i], 3, dims, strides, box, CU_TENSOR_MAP_SWIZZLE_128B, CU_TENSOR_MAP_L2_PROMOTION_L2_256B);
    }
    {
        cuuint32_t box[2] = {32, 192};
        cuuint64_t dq[2] = {4096, DM}, sq[1] = {4096 * 2};
        make_map(enc, &maps.wq, d_in[3], 2, dq, sq, box, CU_TENSOR_MAP_SWIZZLE_64B, CU_TENSOR_MAP_L2_PROMOTION_L2_128B);
        cuuint64_t df[2] = {FF, DM}, sf[1] = {FF * 2};
        make_map(enc, &maps.wg, d_in[6], 2, df, sf, box, CU_TENSOR_MAP_SWIZZLE_64B, CU_TENSOR_MAP_L2_PROMOTION_L2_128B);
        make_map(enc, &maps.wu, d_in[7], 2, df, sf, box, CU_TENSOR_MAP_SWIZZLE_64B, CU_TENSOR_MAP_L2_PROMOTION_L2_128B);
    }
    {
        cuuint32_t boxo[2] = {72, 64};
        cuuint64_t d_o[2] = {DM, 4096}, s_o[1] = {DM * 2};
        make_map(enc, &maps.wo, d_in[4], 2, d_o, s_o, boxo, CU_TENSOR_MAP_SWIZZLE_NONE, CU_TENSOR_MAP_L2_PROMOTION_L2_128B);
        cuuint32_t boxd[2] = {64, 96};
        cuuint64_t d_d[2] = {DM, FF}, s_d[1] = {DM * 2};
        make_map(enc, &maps.wd, d_in[8], 2, d_d, s_d, boxd, CU_TENSOR_MAP_SWIZZLE_128B, CU_TENSOR_MAP_L2_PROMOTION_L2_128B);
    }
    fused_decode_kernel<<<NCTA, NTHREADS, SMEM_BYTES>>>(maps, (const __nv_bfloat16*)d_in[0], (__nv_bfloat16*)d_out);
}
```

```cpp
#include <cuda_runtime.h>
#include <cuda_bf16.h>
#include <cuda.h>
#include <math.h>
#include <stdint.h>

namespace {

constexpr int NB = 8, DM = 576, HKV = 16, SK = 8192, FF = 4608;
constexpr int NPAIR = NB * HKV;
constexpr int TILE = 64;
constexpr int TPP = SK / TILE;
constexpr int NKV = NPAIR * TPP;
constexpr int NCTA = 132;
constexpr int NST = 4;
constexpr int STAGE = 36864;
constexpr int NUNIT = FF / 32;
constexpr int GRP = 9;
constexpr int NGRP = NUNIT / GRP;
constexpr int NLATE = (NCTA / GRP) * GRP;
constexpr int NEARLY = NUNIT - NLATE;
constexpr int NPLAIN = NCTA - NEARLY;
constexpr int NDYN = NKV - NPLAIN * NST;
constexpr int XP = 584;
constexpr int NTHREADS = 288;

constexpr int INFLIGHT = 3;
constexpr int SPIECES = 4;
constexpr int EPIECES = 4;
constexpr int LATECLAIM = 400;
constexpr int PEEK = 200;
constexpr int MARGIN = 600;
constexpr int TAILPOLL = 900;
constexpr int QDELAY = 800, HDELAY = 700, ODELAY = 400;

constexpr int SM_WBUF = NST * STAGE;
constexpr int SM_XN = SM_WBUF + STAGE;
constexpr int SM_GU = SM_XN + NB * XP * 2;
constexpr int SM_GL = SM_GU + 2 * 8 * 36 * 4;
constexpr int SM_HB = SM_GL + 8 * 36 * 4;
constexpr int SM_RED = SM_HB + 2 * GRP * 32 * 8;
constexpr int SM_PART = SM_RED + 2 * 4 * 36 * 4;
constexpr int SM_OB = SM_PART + 2 * 4 * 40 * 4;
constexpr int SM_BAR = SM_OB + 4 * 512;
constexpr int NBAR = 4 * NST + 29;
constexpr int SM_DESC = SM_BAR + NBAR * 8;
constexpr int SM_TOTAL = SM_DESC + 64;
constexpr int SMEM_BYTES = SM_TOTAL + 1024;

struct Maps { CUtensorMap k, v, wq, wg, wu, wo, wd; };

__device__ __align__(128) unsigned g_queue[32];
__device__ __align__(128) unsigned g_state[32];
__device__ __align__(128) uint32_t g_q[NPAIR * 256];
__device__ __align__(128) uint4 g_ml[NKV * 2];
__device__ __align__(128) uint2 g_po[NPAIR * 2 * 4 * TPP * 8];
__device__ __align__(128) uint4 g_ox[128 * NB * 8];
__device__ __align__(128) uint32_t g_sp[HKV * NB * DM];
__device__ __align__(128) uint32_t g_fp[NGRP * NB * DM];
__device__ __align__(128) uint4 g_h[NUNIT * 2 * 32];

__device__ __forceinline__ uint32_t s2u(const void* p) { return (uint32_t)__cvta_generic_to_shared(p); }
__device__ __forceinline__ void mbar_init(uint32_t b, int c) { asm volatile("mbarrier.init.shared::cta.b64 [%0], %1;" :: "r"(b), "r"(c)); }
__device__ __forceinline__ void mbar_expect(uint32_t b, uint32_t bytes) { asm volatile("mbarrier.arrive.expect_tx.shared::cta.b64 _, [%0], %1;" :: "r"(b), "r"(bytes) : "memory"); }
__device__ __forceinline__ void mbar_arrive(uint32_t b) { asm volatile("mbarrier.arrive.shared::cta.b64 _, [%0];" :: "r"(b) : "memory"); }
__device__ __forceinline__ bool mbar_try(uint32_t b, uint32_t ph) {
    uint32_t ok;
    asm volatile("{\n.reg .pred p;\nmbarrier.try_wait.parity.shared::cta.b64 p, [%1], %2;\nselp.u32 %0, 1, 0, p;\n}" : "=r"(ok) : "r"(b), "r"(ph) : "memory");
    return ok != 0;
}
__device__ __forceinline__ bool mbar_test(uint32_t b, uint32_t ph) {
    uint32_t ok;
    asm volatile("{\n.reg .pred p;\nmbarrier.test_wait.parity.shared::cta.b64 p, [%1], %2;\nselp.u32 %0, 1, 0, p;\n}" : "=r"(ok) : "r"(b), "r"(ph) : "memory");
    return ok != 0;
}
constexpr long long SPIN_LIMIT = 4000000000LL;
__device__ __forceinline__ void mbar_wait(uint32_t b, uint32_t ph) {
    if (mbar_try(b, ph)) return;
    long long t0 = clock64();
    while (!mbar_try(b, ph)) { if (clock64() - t0 > SPIN_LIMIT) __trap(); }
}
struct Spin {
    long long t0 = 0;
    __device__ __forceinline__ void tick() { long long t = clock64(); if (t0 == 0) t0 = t; else if (t - t0 > SPIN_LIMIT) __trap(); }
};
__device__ __forceinline__ void bulk_g2s(uint32_t dst, const void* src, uint32_t bytes, uint32_t bar) {
    asm volatile("cp.async.bulk.shared::cluster.global.mbarrier::complete_tx::bytes [%0], [%1], %2, [%3];" :: "r"(dst), "l"(src), "r"(bytes), "r"(bar) : "memory");
}
__device__ __forceinline__ void tma2d(uint32_t dst, const CUtensorMap* m, int c0, int c1, uint32_t bar) {
    asm volatile("cp.async.bulk.tensor.2d.shared::cluster.global.mbarrier::complete_tx::bytes [%0], [%1, {%3, %4}], [%2];" :: "r"(dst), "l"(m), "r"(bar), "r"(c0), "r"(c1) : "memory");
}
__device__ __forceinline__ void tma3d(uint32_t dst, const CUtensorMap* m, int c0, int c1, int c2, uint32_t bar, uint64_t pol) {
    asm volatile("cp.async.bulk.tensor.3d.shared::cluster.global.mbarrier::complete_tx::bytes.L2::cache_hint [%0], [%1, {%3, %4, %5}], [%2], %6;" :: "r"(dst), "l"(m), "r"(bar), "r"(c0), "r"(c1), "r"(c2), "l"(pol) : "memory");
}
__device__ __forceinline__ void ldsm4(uint32_t (&r)[4], uint32_t a) {
    asm volatile("ldmatrix.sync.aligned.m8n8.x4.shared.b16 {%0,%1,%2,%3}, [%4];" : "=r"(r[0]), "=r"(r[1]), "=r"(r[2]), "=r"(r[3]) : "r"(a));
}
__device__ __forceinline__ void ldsm4t(uint32_t (&r)[4], uint32_t a) {
    asm volatile("ldmatrix.sync.aligned.m8n8.x4.trans.shared.b16 {%0,%1,%2,%3}, [%4];" : "=r"(r[0]), "=r"(r[1]), "=r"(r[2]), "=r"(r[3]) : "r"(a));
}
__device__ __forceinline__ void mma16816(float (&c)[4], const uint32_t (&a)[4], uint32_t b0, uint32_t b1) {
    asm("mma.sync.aligned.m16n8k16.row.col.f32.bf16.bf16.f32 {%0,%1,%2,%3}, {%4,%5,%6,%7}, {%8,%9}, {%0,%1,%2,%3};"
                 : "+f"(c[0]), "+f"(c[1]), "+f"(c[2]), "+f"(c[3]) : "r"(a[0]), "r"(a[1]), "r"(a[2]), "r"(a[3]), "r"(b0), "r"(b1));
}
__device__ __forceinline__ uint4 ld_relaxed4(const void* p) {
    uint4 v; asm volatile("ld.relaxed.gpu.global.v4.u32 {%0,%1,%2,%3}, [%4];" : "=r"(v.x), "=r"(v.y), "=r"(v.z), "=r"(v.w) : "l"(p) : "memory"); return v;
}
__device__ __forceinline__ uint2 ld_relaxed2(const void* p) {
    uint2 v; asm volatile("ld.relaxed.gpu.global.v2.u32 {%0,%1}, [%2];" : "=r"(v.x), "=r"(v.y) : "l"(p) : "memory"); return v;
}
__device__ __forceinline__ uint32_t ld_relaxed1(const void* p) {
    uint32_t v; asm volatile("ld.relaxed.gpu.global.u32 %0, [%1];" : "=r"(v) : "l"(p) : "memory"); return v;
}
__device__ __forceinline__ void st_relaxed4(void* p, uint32_t a, uint32_t b, uint32_t c, uint32_t d) {
    asm volatile("st.relaxed.gpu.global.v4.u32 [%0], {%1,%2,%3,%4};" :: "l"(p), "r"(a), "r"(b), "r"(c), "r"(d) : "memory");
}
__device__ __forceinline__ void st_relaxed1(void* p, uint32_t a) {
    asm volatile("st.relaxed.gpu.global.u32 [%0], %1;" :: "l"(p), "r"(a) : "memory");
}
__device__ __forceinline__ void st_relaxed2(void* p, uint32_t a, uint32_t b) {
    asm volatile("st.relaxed.gpu.global.v2.u32 [%0], {%1,%2};" :: "l"(p), "r"(a), "r"(b) : "memory");
}
__device__ __forceinline__ uint4 lds128(uint32_t a) { uint4 v; asm volatile("ld.shared.v4.u32 {%0,%1,%2,%3}, [%4];" : "=r"(v.x), "=r"(v.y), "=r"(v.z), "=r"(v.w) : "r"(a) : "memory"); return v; }
__device__ __forceinline__ void bar_cons() { asm volatile("bar.sync 1, 128;" ::: "memory"); }
__device__ __forceinline__ void bar_comb() { asm volatile("bar.sync 2, 128;" ::: "memory"); }
__device__ __forceinline__ float bfr(float v) { return __bfloat162float(__float2bfloat16_rn(v)); }
__device__ __forceinline__ uint32_t pack_bf16(float lo, float hi) {
    uint32_t r; asm("cvt.rn.bf16x2.f32 %0, %1, %2;" : "=r"(r) : "f"(hi), "f"(lo)); return r;
}
__device__ __forceinline__ float ex2(float x) { float y; asm("ex2.approx.ftz.f32 %0, %1;" : "=f"(y) : "f"(x)); return y; }
__device__ __forceinline__ float silu_f(float v) { return __fdividef(v, 1.0f + __expf(-v)); }
__device__ __forceinline__ uint32_t tagf(float v, uint32_t tag) { return (__float_as_uint(v) & ~1u) | tag; }
__device__ __forceinline__ float untagf(uint32_t w) { return __uint_as_float(w & ~1u); }
__device__ __forceinline__ uint32_t bad4(const uint4& v, uint32_t tag) { return ((v.x ^ tag) | (v.y ^ tag) | (v.z ^ tag) | (v.w ^ tag)) & 1u; }
__device__ __forceinline__ uint32_t pack_tag(float lo, float hi, uint32_t tag) {
    uint32_t l = ((__float_as_uint(lo) + 0x10000u) >> 16) & 0xFFFEu;
    uint32_t h = pack_bf16(0.f, hi) & 0xFFFF0000u;
    return h | l | tag;
}

__device__ __forceinline__ int dyn_tile(int n) { return n + NPLAIN * NST; }

__device__ __forceinline__ uint32_t addr_w32(uint32_t base, int lane, int mt, int ks) {
    int mat = lane >> 3, row = ks * 16 + (mat >> 1) * 8 + (lane & 7), c = mt * 2 + (mat & 1);
    return base + row * 64 + ((c ^ ((row >> 1) & 3)) << 4);
}
__device__ __forceinline__ uint32_t addr_kv(uint32_t base, int key, int chunk) {
    return base + (chunk >> 3) * 8192 + key * 128 + (((chunk & 7) ^ (key & 7)) << 4);
}

template <int NKS>
__device__ __forceinline__ void proj32(float (&acc)[4], uint32_t wbase, uint32_t bar, uint32_t xn, int lane, int mt, int ks0) {
    uint32_t xb[NKS / 2][4];
    const uint32_t xa = xn + ((lane & 7) * XP + (lane >> 3) * 8 + ks0 * 16) * 2;
#pragma unroll
    for (int i = 0; i < NKS / 2; i++) ldsm4(xb[i], xa + i * 64);
    float a4[4][4];
#pragma unroll
    for (int i = 0; i < 4; i++) { a4[i][0] = a4[i][1] = a4[i][2] = a4[i][3] = 0.f; }
    const uint32_t wa = addr_w32(wbase, lane, mt, ks0);
    if (ks0 < 12) mbar_wait(bar, 0);
    mbar_wait(bar + 8, 0);
    if (ks0 + NKS > 24) mbar_wait(bar + 16, 0);
#pragma unroll
    for (int i = 0; i < NKS; i++) {
        uint32_t a[4];
        ldsm4t(a, wa + i * 1024);
        mma16816(a4[i & 3], a, xb[i >> 1][(i & 1) * 2], xb[i >> 1][(i & 1) * 2 + 1]);
    }
#pragma unroll
    for (int i = 0; i < 4; i++) acc[i] = (a4[0][i] + a4[1][i]) + (a4[2][i] + a4[3][i]);
}

__device__ __forceinline__ void put_frag(float* dst, const float (&acc)[4], int mt, int g, int t) {
    dst[(2 * t) * 36 + mt * 16 + g] = acc[0];
    dst[(2 * t + 1) * 36 + mt * 16 + g] = acc[1];
    dst[(2 * t) * 36 + mt * 16 + g + 8] = acc[2];
    dst[(2 * t + 1) * 36 + mt * 16 + g + 8] = acc[3];
}
__device__ __forceinline__ void put_tile(uint32_t* dst, uint32_t w0, uint32_t w1, uint32_t w2, uint32_t w3, bool upper) {
    st_relaxed1(dst, w0); st_relaxed1(dst + DM, w1);
    if (upper) { st_relaxed1(dst + 8, w2); st_relaxed1(dst + DM + 8, w3); }
}
__device__ __forceinline__ uint32_t* fp_slot(int unit, int warp, int g, int t) {
    return g_fp + ((unit / GRP) * NB + 2 * t) * DM + (unit % GRP) * 64 + warp * 16 + g;
}

template <bool LATE>
__device__ __forceinline__ void ffn_unit(uint32_t sb, uint32_t bufG, uint32_t bufU, uint32_t bufD, uint32_t barG, uint32_t barU,
                                         uint32_t barD, int unit, int warp, int lane, uint32_t tag) {
    const int g = lane >> 2, t = lane & 3;
    const int hf = warp >> 1, mt = warp & 1;
    float* gu = reinterpret_cast<float*>(__cvta_shared_to_generic(sb + SM_GU));
    float acc[4];
    if (LATE) { mbar_wait(barG, 0); proj32<18>(acc, bufU, barU, sb + SM_XN, lane, mt, hf * 18); }
    else proj32<36>(acc, hf ? bufU : bufG, hf ? barU : barG, sb + SM_XN, lane, mt, 0);
    put_frag(gu + hf * 288, acc, mt, g, t);
    bar_cons();
    if (warp < 2) {
        uint32_t hw[2];
#pragma unroll
        for (int j = 0; j < 2; j++) {
            const int f = g * 36 + warp * 16 + j * 8 + 2 * t;
            const float2 p0 = *reinterpret_cast<const float2*>(gu + f), p1 = *reinterpret_cast<const float2*>(gu + 288 + f);
            float2 gg = p0, uu = p1;
            if (LATE) { gg = *reinterpret_cast<const float2*>(gu + 576 + f); uu = make_float2(p0.x + p1.x, p0.y + p1.y); }
            hw[j] = pack_bf16(bfr(silu_f(bfr(gg.x))) * bfr(uu.x), bfr(silu_f(bfr(gg.y))) * bfr(uu.y));
        }
        st_relaxed4(g_h + (unit * 2 + warp) * 32 + lane, (hw[0] << 16) | tag, (hw[0] & 0xFFFF0000u) | tag, (hw[1] << 16) | tag, (hw[1] & 0xFFFF0000u) | tag);
    }
    {
        const uint4* src = g_h + (unit / GRP) * (2 * GRP * 32) + warp * 32 + lane;
        uint4 v[5];
        uint32_t pend = warp < 2 ? 0x1Fu : 0xFu;
        Spin sp;
        if (LATE) __nanosleep(HDELAY);
        while (true) {
#pragma unroll
            for (int i = 0; i < 5; i++)
                if (pend >> i & 1) v[i] = ld_relaxed4(src + i * 128);
#pragma unroll
            for (int i = 0; i < 5; i++)
                if ((pend >> i & 1) && !__any_sync(~0u, bad4(v[i], tag))) {
                    pend &= ~(1u << i);
                    asm volatile("st.shared.v2.u32 [%0], {%1, %2};" :: "r"(sb + SM_HB + ((i * 4 + warp) * 32 + lane) * 8),
                                 "r"(__byte_perm(v[i].x, v[i].y, 0x7632)), "r"(__byte_perm(v[i].z, v[i].w, 0x7632)) : "memory");
                }
            if (!pend) break;
            __nanosleep(30);
            sp.tick();
        }
    }
    mbar_wait(barD, 0); mbar_wait(barD + 8, 0); mbar_wait(barD + 16, 0);
    uint32_t a[2 * GRP][4];
    {
        const int m4 = lane >> 3, row = (m4 >> 1) * 8 + (lane & 7), c = warp * 2 + (m4 & 1);
        const uint32_t a0 = bufD + row * 128 + ((c ^ (lane & 7)) << 4);
#pragma unroll
        for (int ks = 0; ks < 2 * GRP; ks++) ldsm4t(a[ks], a0 + ks * 2048);
    }
    bar_cons();
    float c0[4] = {0.f, 0.f, 0.f, 0.f}, c1[4] = {0.f, 0.f, 0.f, 0.f}, c2[4] = {0.f, 0.f, 0.f, 0.f};
#pragma unroll
    for (int ks = 0; ks < 2 * GRP; ks++) {
        uint32_t h0, h1;
        asm volatile("ld.shared.v2.u32 {%0, %1}, [%2];" : "=r"(h0), "=r"(h1) : "r"(sb + SM_HB + (ks * 32 + lane) * 8) : "memory");
        mma16816(ks % 3 == 0 ? c0 : ks % 3 == 1 ? c1 : c2, a[ks], h0, h1);
    }
    put_tile(fp_slot(unit, warp, g, t), tagf(c0[0] + c1[0] + c2[0], tag), tagf(c0[1] + c1[1] + c2[1], tag),
             tagf(c0[2] + c1[2] + c2[2], tag), tagf(c0[3] + c1[3] + c2[3], tag), true);
}

__device__ __forceinline__ void gather16(const uint32_t* base, float* red, int tid, uint32_t tag) {
    const int f = tid & 7;
    const uint32_t* src = base + (tid >> 3) * (NB * DM) + f * 4;
    uint4 v0, v1 = make_uint4(tag, tag, tag, tag);
    Spin sp;
    while (true) {
        v0 = ld_relaxed4(src);
        if (f == 0) v1 = ld_relaxed4(src + 32);
        if (!__any_sync(~0u, bad4(v0, tag) | bad4(v1, tag))) break;
        __nanosleep(30);
        sp.tick();
    }
    float a[8] = {untagf(v0.x), untagf(v0.y), untagf(v0.z), untagf(v0.w), untagf(v1.x), untagf(v1.y), untagf(v1.z), untagf(v1.w)};
#pragma unroll
    for (int i = 0; i < 8; i++) { a[i] += __shfl_xor_sync(~0u, a[i], 8); a[i] += __shfl_xor_sync(~0u, a[i], 16); }
    if ((tid & 31) < 8) {
        float* r = red + (tid >> 5) * 36;
        *reinterpret_cast<float4*>(r + f * 4) = make_float4(a[0], a[1], a[2], a[3]);
        if (f == 0) *reinterpret_cast<float4*>(r + 32) = make_float4(a[4], a[5], a[6], a[7]);
    }
}

__global__ void __launch_bounds__(NTHREADS, 1)
fused_decode_kernel(const __grid_constant__ Maps maps, const __nv_bfloat16* __restrict__ x, __nv_bfloat16* __restrict__ out) {
    extern __shared__ uint8_t smem_raw[];
    const uint32_t sb = (s2u(smem_raw) + 1023u) & ~1023u;
    uint8_t* sg = smem_raw + (sb - s2u(smem_raw));
    const int tid = threadIdx.x, warp = tid >> 5, lane = tid & 31, cta = blockIdx.x;
    const uint32_t bar_full = sb + SM_BAR, bar_empty = bar_full + NST * 8;
    const uint32_t bar_q = bar_empty + NST * 8, bar_v = bar_q + NST * 8;
    const uint32_t bar_wq = bar_v + NST * 8, bar_wg = bar_wq + 24;
    const uint32_t bar_e = bar_wg + 24;
    const uint32_t bar_lu = bar_e + 72, bar_ld = bar_lu + 24, bar_wo = bar_ld + 24;
    const uint32_t bar_ssum = bar_wo + 32, bar_first = bar_ssum + 8, bar_wfree = bar_first + 8, bar_gdone = bar_wfree + 8;
    volatile int* desc = reinterpret_cast<volatile int*>(sg + SM_DESC);

    uint32_t xr[2][9];
    if (warp < NST) {
#pragma unroll
        for (int r = 0; r < 2; r++)
#pragma unroll
            for (int i = 0; i < 9; i++)
                asm volatile("ld.global.nc.u32 %0, [%1];" : "=r"(xr[r][i]) : "l"(reinterpret_cast<const uint32_t*>(x + (warp * 2 + r) * DM) + i * 32 + lane));
    }
    if (tid >= 160 && tid < 167) asm volatile("prefetch.tensormap [%0];" :: "l"(reinterpret_cast<const CUtensorMap*>(&maps) + (tid - 160)) : "memory");
    uint32_t epoch = 0;
    if (warp != NST) epoch = ld_relaxed1(&g_state[1]);
    if (tid == NST * 32) {
        mbar_init(bar_wq, 1); mbar_init(bar_wq + 8, 1); mbar_init(bar_wq + 16, 1); mbar_init(bar_full, 1); mbar_init(bar_e, 1);
        asm volatile("fence.mbarrier_init.release.cluster;" ::: "memory");
        if (cta < 128) {
#pragma unroll
            for (int i = 0; i < 3; i++) { mbar_expect(bar_wq + i * 8, 12288); tma2d(sb + SM_WBUF + i * 12288, &maps.wq, cta * 32, i * 192, bar_wq + i * 8); }
        }
        if (cta >= NPLAIN) { mbar_expect(bar_e, 12288); tma2d(sb, &maps.wg, (NLATE + cta - NPLAIN) * 32, 0, bar_e); }
        else {
            uint64_t pol; asm volatile("createpolicy.fractional.L2::evict_first.b64 %0, 1.0;" : "=l"(pol));
            mbar_expect(bar_full, 16384);
            tma3d(sb, &maps.k, 0, cta * TILE, 0, bar_full, pol);
        }
    }

    if (warp == NST) {
        uint64_t pol; asm volatile("createpolicy.fractional.L2::evict_first.b64 %0, 1.0;" : "=l"(pol));
        constexpr int FN = 4, F0 = FN - INFLIGHT;
        uint32_t fifo[FN];
#pragma unroll
        for (int i = 0; i < FN; i++) fifo[i] = 0;
        auto gate = [&](int n) { for (int i = F0; i < F0 + n; i++) if (fifo[i]) mbar_wait(fifo[i] & ~1u, fifo[i] & 1u); };
        auto push = [&](uint32_t bar, uint32_t par) {
#pragma unroll
            for (int i = 0; i + 1 < FN; i++) fifo[i] = fifo[i + 1];
            fifo[FN - 1] = bar | par;
        };
        auto issue_half = [&](const CUtensorMap* m, int tile, uint32_t dst, uint32_t bar, uint32_t par) {
            mbar_expect(bar, 16384);
            tma3d(dst, m, 0, tile * TILE, 0, bar, pol);
            push(bar, par);
        };
        auto issue_k = [&](int tile, int st, uint32_t par) { desc[st] = tile; issue_half(&maps.k, tile, sb + st * STAGE, bar_full + st * 8, par); };
        auto issue_v = [&](int tile, int st, uint32_t par) { issue_half(&maps.v, tile, sb + st * STAGE + 16384, bar_v + st * 8, par); };
        auto piece = [&](const CUtensorMap* m, int c0, int c1, uint32_t dst, uint32_t bar, uint32_t bytes) {
            mbar_expect(bar, bytes);
            tma2d(dst, m, c0, c1, bar);
            push(bar, 0);
        };
        auto col_piece = [&](const CUtensorMap* m, int unit, int i, uint32_t buf, uint32_t bar) { piece(m, unit * 32, i * 192, buf + i * 12288, bar + i * 8, 12288); };
        auto down_piece = [&](int unit, int i, uint32_t buf, uint32_t bar) {
            piece(&maps.wd, (unit % GRP) * 64, (unit / GRP) * (GRP * 32) + i * 96, buf + i * 12288, bar + i * 8, 12288);
        };
        auto gate4 = [&]() { const uint32_t f = fifo[FN - SPIECES]; if (f) mbar_wait(f & ~1u, f & 1u); };
        const bool early = cta >= NPLAIN;
        const int eunit = NLATE + cta - NPLAIN;
        int next = 0;
        auto claim = [&]() { return (int)atomicAdd(&g_queue[0], 1u); };
        if (lane == 0) {
            if (cta < 128) for (int i = 0; i < 3; i++) push(bar_wq + i * 8, 0);
            push(early ? bar_e : bar_full, 0);
            next = claim();
            desc[0] = cta; desc[9] = 0;
#pragma unroll
            for (int i = 1; i < NBAR; i++) {
                const int o = i * 8;
                if (o >= 4 * NST * 8 && o < 4 * NST * 8 + 24) continue;
                if (o == 4 * NST * 8 + 48) continue;
                mbar_init(bar_full + o, bar_full + o == bar_ssum ? 4 : bar_full + o == bar_gdone ? 2 : 1);
            }
            asm volatile("fence.mbarrier_init.release.cluster;" ::: "memory");
        }
        __syncwarp();
        asm volatile("bar.arrive 3, %0;" :: "n"(NTHREADS) : "memory");
        if (lane == 0) {
            if (early) {
                for (int i = 1; i < 3; i++) { gate4(); col_piece(&maps.wg, eunit, i, sb, bar_e); }
                for (int i = 0; i < 3; i++) { gate4(); col_piece(&maps.wu, eunit, i, sb + STAGE, bar_e + 24); }
                for (int i = 0; i < 3; i++) { gate4(); down_piece(eunit, i, sb + 2 * STAGE, bar_e + 48); }
                const int tile = dyn_tile(next);
                gate4(); issue_k(tile, 3, 0); mbar_arrive(bar_first);
                next = claim();
                gate4(); issue_v(tile, 3, 0);
            } else {
                gate4(); issue_v(cta, 0, 0);
#pragma unroll
                for (int i = 1; i < NST; i++) { gate4(); issue_k(cta + i * NPLAIN, i, 0); gate4(); issue_v(cta + i * NPLAIN, i, 0); }
            }
            if (cta < 128) mbar_wait(bar_wfree, 0);
            if (cta < NLATE) for (int i = 0; i < 3; i++) { gate4(); col_piece(&maps.wg, cta, i, sb + SM_WBUF, bar_wg); }
            if (early) mbar_wait(bar_q + 24, 0);
            int st = 0; uint32_t ph = 0;
            while (true) {
                if (next < 0) {
                    Spin sp;
                    while (!mbar_test(fifo[F0] & ~1u, fifo[F0] & 1u)) {
                        if (desc[9] >= NDYN - PEEK && ld_relaxed1(&g_queue[0]) >= (unsigned)NDYN) { next = NDYN; break; }
                        __nanosleep(100);
                        sp.tick();
                    }
                    if (next >= NDYN) break;
                    mbar_wait(bar_empty + st * 8, ph);
                    next = claim();
                } else {
                    gate(1);
                    mbar_wait(bar_empty + st * 8, ph);
                }
                if (next >= NDYN) break;
                const int tile = dyn_tile(next);
                const uint32_t par = (early && st < 3) ? ph : ph ^ 1u;
                issue_k(tile, st, par);
                desc[9] = next;
                mbar_expect(bar_q + st * 8, 1024);
                bulk_g2s(sb + st * STAGE + 32768, g_q + (tile / TPP) * 256, 1024, bar_q + st * 8);
                next = next >= NDYN - LATECLAIM ? -1 : claim();
                if (next >= 0) gate(1);
                issue_v(tile, st, par);
                if (++st == NST) { st = 0; ph ^= 1; }
            }
            desc[9] = NDYN;
            const int stU = st;
            desc[4] = stU;
#pragma unroll
            for (int i = 0; i < F0; i++) fifo[i] = 0;
            int ends = 0, k = cta < NLATE ? 0 : 6;
            const int kend = cta < 128 ? 10 : 6;
            if (cta < NLATE) mbar_wait(bar_gdone, 0);
            Spin sp;
            while (ends < NST || k < kend) {
                if (ends < NST && mbar_test(bar_empty + st * 8, ph)) {
#pragma unroll
                    for (int i = 0; i < FN; i++) if ((fifo[i] & ~1u) == bar_full + st * 8) fifo[i] = 0;
                    desc[st] = -1;
                    mbar_arrive(bar_full + st * 8);
                    if (++st == NST) { st = 0; ph ^= 1; }
                    ends++;
                }
                const uint32_t f = fifo[FN - EPIECES];
                if (k < kend && ends >= (k < 3 ? 1 : k < 6 ? 2 : 0) && (f == 0 || mbar_test(f & ~1u, f & 1u))) {
                    if (k < 3) col_piece(&maps.wu, cta, k, sb + stU * STAGE, bar_lu);
                    else if (k < 6) down_piece(cta, k - 3, sb + ((stU + 1) % NST) * STAGE, bar_ld);
                    else piece(&maps.wo, (cta & 7) * 72, (cta >> 3) * 256 + (k - 6) * 64, sb + SM_WBUF + (k - 6) * 9216, bar_wo + (k - 6) * 8, 9216);
                    k++;
                }
                sp.tick();
            }
            if (atomicAdd(&g_state[0], 1u) == NCTA - 1) {
                g_queue[0] = 0; g_state[0] = 0;
                g_state[1] = g_state[1] + 1;
            }
        }
    } else if (warp < NST) {
        const int g = lane >> 2, t = lane & 3;
        float xfin = 0.f;
        if (tid < 36 && cta < 128) xfin = __bfloat162float(x[cta * 36 + tid]);
        {
#pragma unroll
            for (int r = 0; r < 2; r++) {
                float v[18], s = 0.f;
#pragma unroll
                for (int i = 0; i < 9; i++) { v[2 * i] = __uint_as_float(xr[r][i] << 16); v[2 * i + 1] = __uint_as_float(xr[r][i] & 0xFFFF0000u); s += v[2 * i] + v[2 * i + 1]; }
#pragma unroll
                for (int o = 16; o; o >>= 1) s += __shfl_xor_sync(~0u, s, o);
                const float mean = s * (1.0f / DM);
                float q = 0.f;
#pragma unroll
                for (int i = 0; i < 18; i++) { float d = v[i] - mean; q += d * d; }
#pragma unroll
                for (int o = 16; o; o >>= 1) q += __shfl_xor_sync(~0u, q, o);
                const float mb = bfr(mean), rden = __frcp_rn(bfr(__fsqrt_rn(bfr(bfr(q * (1.0f / DM)) + 1e-5f))));
                uint32_t* xn = reinterpret_cast<uint32_t*>(sg + SM_XN) + (warp * 2 + r) * (XP / 2);
#pragma unroll
                for (int i = 0; i < 9; i++) xn[i * 32 + lane] = pack_bf16(bfr(v[2 * i] - mb) * rden, bfr(v[2 * i + 1] - mb) * rden);
            }
        }
        const uint32_t tag = (epoch & 1u) ^ 1u;
        asm volatile("bar.sync 3, %0;" :: "n"(NTHREADS), "r"(tag) : "memory");
        if (cta < 128) {
            float acc[4];
            const int mt = warp & 1, kh = warp >> 1;
            proj32<18>(acc, sb + SM_WBUF, bar_wq, sb + SM_XN, lane, mt, kh * 18);
            float* gu = reinterpret_cast<float*>(sg + SM_GU);
            put_frag(gu + kh * 288, acc, mt, g, t);
            bar_cons();
            {
                const int b = tid >> 4, c = (tid & 15) * 2;
                const float q0 = gu[b * 36 + c] + gu[(8 + b) * 36 + c], q1 = gu[b * 36 + c + 1] + gu[(8 + b) * 36 + c + 1];
                const int hq = cta >> 2, d = (cta & 3) * 32 + c;
                const int off = (b * HKV + (hq >> 1)) * 256 + (hq & 1) * 128 + (d >> 4) * 16 + ((d & 7) >> 1) * 4 + ((d >> 3) & 1) * 2;
                const uint32_t pk = pack_bf16(q0, q1);
                st_relaxed2(g_q + off, (pk << 16) | tag, (pk & 0xFFFF0000u) | tag);
            }
            bar_cons();
            if (tid == 0) mbar_arrive(bar_wfree);
        }
        if (cta >= NPLAIN) {
            ffn_unit<false>(sb, sb, sb + STAGE, sb + 2 * STAGE, bar_e, bar_e + 24, bar_e + 48, NLATE + cta - NPLAIN, warp, lane, tag);
            bar_cons();
            if (warp < 3 && lane == 0) mbar_arrive(bar_empty + warp * 8);
        }
        const uint32_t kb = sb + warp * STAGE, vb = kb + 16384, qb = kb + 32768;
        const int mat = lane >> 3, r8 = lane & 7;
        const int kkey = (mat & 1) ? 8 + ((r8 + 4) & 7) : r8;
        const int rho = (r8 >> 1) + (mat >> 1) * 4;
        const int vkey = (r8 & 1) ? 8 + ((rho + 4) & 7) : rho;
        const float sc = 1.4426950408889634f;
        uint32_t ph = 0;
        while (true) {
            mbar_wait(bar_full + warp * 8, ph);
            ph ^= 1;
            const int tile = desc[warp];
            if (tile < 0) break;
            mbar_wait(bar_q + warp * 8, ph ^ 1u);
            uint32_t qf[16];
            {
                const bool on = (g == 0) || (g == 2);
                uint4 v[8];
                uint32_t bad = 0;
#pragma unroll
                for (int j = 0; j < 8; j++) {
                    v[j] = make_uint4(tag, tag, tag, tag);
                    if (on) v[j] = lds128(qb + (g >> 1) * 512 + j * 64 + t * 16);
                    bad |= (v[j].x ^ tag) | (v[j].y ^ tag) | (v[j].z ^ tag) | (v[j].w ^ tag);
                }
                if (__any_sync(~0u, bad & 1u)) {
                    Spin sp;
                    do {
                        bad = 0;
                        if (on) {
#pragma unroll
                            for (int j = 0; j < 8; j++) v[j] = ld_relaxed4(g_q + (tile / TPP) * 256 + (g >> 1) * 128 + j * 16 + t * 4);
#pragma unroll
                            for (int j = 0; j < 8; j++) bad |= bad4(v[j], tag);
                        }
                        sp.tick();
                    } while (__any_sync(~0u, bad));
                }
#pragma unroll
                for (int j = 0; j < 8; j++) { qf[2 * j] = __byte_perm(v[j].x, v[j].y, 0x7632); qf[2 * j + 1] = __byte_perm(v[j].z, v[j].w, 0x7632); }
            }
            float s[4][4];
#pragma unroll
            for (int mt = 0; mt < 4; mt++) { s[mt][0] = s[mt][1] = s[mt][2] = s[mt][3] = 0.f; }
#pragma unroll
            for (int ks = 0; ks < 8; ks++)
#pragma unroll
                for (int mt = 0; mt < 4; mt++) {
                    uint32_t a[4];
                    ldsm4(a, addr_kv(kb, mt * 16 + kkey, 2 * ks + (mat >> 1)));
                    mma16816(s[mt], a, qf[2 * ks], qf[2 * ks + 1]);
                }
#pragma unroll
            for (int mt = 0; mt < 4; mt++) {
                const uint32_t r1 = pack_bf16(s[mt][0], s[mt][2]);
                const uint32_t r2 = pack_bf16(__uint_as_float(r1 << 16) * 0.08838834764831845f, __uint_as_float(r1 & 0xFFFF0000u) * 0.08838834764831845f);
                s[mt][0] = __uint_as_float(r2 << 16); s[mt][2] = __uint_as_float(r2 & 0xFFFF0000u);
            }
            float m = fmaxf(fmaxf(fmaxf(s[0][0], s[0][2]), fmaxf(s[1][0], s[1][2])), fmaxf(fmaxf(s[2][0], s[2][2]), fmaxf(s[3][0], s[3][2])));
            m = fmaxf(m, __shfl_xor_sync(~0u, m, 4));
            m = fmaxf(m, __shfl_xor_sync(~0u, m, 8));
            m = fmaxf(m, __shfl_xor_sync(~0u, m, 16));
            const float ms = untagf(__float_as_uint(m * sc));
            float l = 0.f;
            uint32_t pb[4][2];
#pragma unroll
            for (int mt = 0; mt < 4; mt++) {
                const float p0 = ex2(fmaf(s[mt][0], sc, -ms)), p1 = ex2(fmaf(s[mt][2], sc, -ms));
                l += p0 + p1;
                const uint32_t pk = pack_bf16(p0, p1);
                pb[mt][0] = __shfl_sync(~0u, pk, 4 * t + (g & 1));
                pb[mt][1] = __shfl_sync(~0u, pk, 4 * (t + 4) + (g & 1));
            }
            l += __shfl_xor_sync(~0u, l, 4);
            l += __shfl_xor_sync(~0u, l, 8);
            l += __shfl_xor_sync(~0u, l, 16);
            float o[8][4];
#pragma unroll
            for (int i = 0; i < 8; i++) { o[i][0] = o[i][1] = o[i][2] = o[i][3] = 0.f; }
            mbar_wait(bar_v + warp * 8, ph ^ 1u);
#pragma unroll
            for (int kk = 0; kk < 4; kk++)
#pragma unroll
                for (int i = 0; i < 8; i++) {
                    uint32_t a[4];
                    ldsm4t(a, addr_kv(vb, kk * 16 + vkey, 2 * i + (mat & 1)));
                    mma16816(o[i], a, pb[kk][0], pb[kk][1]);
                }
            __syncwarp();
            if (lane == 0) mbar_arrive(bar_empty + warp * 8);
            const float inv = __fdividef(1.0f, l);
            const float inv1 = __shfl_down_sync(~0u, inv, 1);
            const int pair = tile / TPP, tt = tile % TPP;
            if (t == 0) {
                uint2* dst = g_po + ((size_t)pair * 8 * TPP + tt) * 8 + g;
#pragma unroll
                for (int qd = 0; qd < 4; qd++) {
                    st_relaxed2(dst + (size_t)qd * TPP * 8,
                                pack_tag(o[2 * qd][0] * inv, o[2 * qd][2] * inv, tag), pack_tag(o[2 * qd + 1][0] * inv, o[2 * qd + 1][2] * inv, tag));
                    st_relaxed2(dst + (size_t)(4 + qd) * TPP * 8,
                                pack_tag(o[2 * qd][1] * inv1, o[2 * qd][3] * inv1, tag), pack_tag(o[2 * qd + 1][1] * inv1, o[2 * qd + 1][3] * inv1, tag));
                }
            }
            {
                const uint32_t m_ = tagf(ms, tag), l_ = tagf(l, tag);
                const uint32_t m0 = __shfl_sync(~0u, m_, 0), l0 = __shfl_sync(~0u, l_, 0), m1 = __shfl_sync(~0u, m_, 1), l1 = __shfl_sync(~0u, l_, 1);
                if (lane < 2) st_relaxed4(g_ml + tile * 2 + lane, m0, l0, m1, l1);
            }
        }
        if (cta < NLATE) {
            {
                const uint32_t inv = tag ^ 1u;
                put_tile(fp_slot(cta, warp, g, t), inv, inv, inv, inv, true);
                if (warp < 2) st_relaxed4(g_h + (cta * 2 + warp) * 32 + lane, inv, inv, inv, inv);
            }
            const int stU = desc[4];
            ffn_unit<true>(sb, 0, sb + stU * STAGE, sb + ((stU + 1) % NST) * STAGE, bar_gdone, bar_lu, bar_ld, cta, warp, lane, tag);
        }
        if (cta < 128) {
            float* red = reinterpret_cast<float*>(sg + SM_RED);
            gather16(g_fp + cta * 36, red, tid, tag);
            bar_cons();
            if (tid < 36) {
                const float f = (red[tid] + red[36 + tid]) + (red[72 + tid] + red[108 + tid]);
                const float gate = bfr(silu_f(bfr(f)));
                mbar_wait(bar_ssum, 0);
                const float s = bfr((red[144 + tid] + red[180 + tid]) + (red[216 + tid] + red[252 + tid]));
                out[cta * 36 + tid] = __float2bfloat16_rn(xfin + bfr(s * gate));
            }
        }
    } else {
        const int cw = warp - NST - 1, ctid = tid - (NST + 1) * 32;
        const uint32_t tag = (epoch & 1u) ^ 1u;
        {
            const bool early = cta >= NPLAIN;
            asm volatile("bar.sync 3, %0;" :: "n"(NTHREADS), "r"(tag) : "memory");
            if (!early || cw == 3) {
                int tile = cta + cw * NPLAIN;
                if (early) {
                    mbar_wait(bar_first, 0);
                    tile = desc[3];
                } else {
                    mbar_wait(bar_wfree, 0);
                    __nanosleep(QDELAY);
                }
                const uint32_t* src = g_q + (tile / TPP) * 256 + lane * 4;
                uint4 v0, v1;
                Spin sp;
                while (true) {
                    v0 = ld_relaxed4(src); v1 = ld_relaxed4(src + 128);
                    if (!__any_sync(~0u, bad4(v0, tag) | bad4(v1, tag))) break;
                    __nanosleep(200);
                    sp.tick();
                }
                uint4* dst = reinterpret_cast<uint4*>(sg + cw * STAGE + 32768) + lane;
                dst[0] = v0; dst[32] = v1;
                __syncwarp();
                if (lane == 0) mbar_arrive(bar_q + cw * 8);
            }
            if (cw < 2 && cta < NLATE) {
                float acc[4];
                proj32<36>(acc, sb + SM_WBUF, bar_wg, sb + SM_XN, lane, cw, 0);
                put_frag(reinterpret_cast<float*>(sg + SM_GL), acc, cw, lane >> 2, lane & 3);
                __syncwarp();
                if (lane == 0) mbar_arrive(bar_gdone);
            }
        }
        if (cta < 128) {
            const int g = lane >> 2, t = lane & 3;
            const int hkv = cta >> 3, head = (cta >> 2) & 1, qd = cta & 3;
            uint32_t* sdst = g_sp + (hkv * NB + 2 * t) * DM + (cta & 7) * 72 + cw * 16 + g;
            const uint4* oxs = g_ox + (hkv * 8 * NB + g) * 8 + t;
            uint32_t ob[16][2];
            auto collect_o = [&](bool on) {
                uint4 v[16];
                Spin sp;
                while (true) {
                    uint32_t bad = 0;
                    if (on) {
#pragma unroll
                        for (int i = 0; i < 16; i++) v[i] = ld_relaxed4(oxs + (i >> 1) * (NB * 8) + (i & 1) * 4);
#pragma unroll
                        for (int i = 0; i < 16; i++) bad |= bad4(v[i], tag);
                    }
                    if (!__any_sync(~0u, bad)) break;
                    __nanosleep(30);
                    sp.tick();
                }
                if (on) {
#pragma unroll
                    for (int i = 0; i < 16; i++) { ob[i][0] = __byte_perm(v[i].x, v[i].y, 0x7632); ob[i][1] = __byte_perm(v[i].z, v[i].w, 0x7632); }
                }
            };
#pragma unroll 1
            for (int b = 0; b < NB; b++) {
                const int p = b * HKV + hkv;
                uint2 e;
                uint4 v[4];
                const uint2* rows = g_po + ((size_t)((p * 2 + head) * 4 + qd) * TPP + cw * 32 + g) * 8 + t * 2;
                {
                    const uint2* mlp = reinterpret_cast<const uint2*>(g_ml + (p * TPP + cw * 32 + lane) * 2) + head;
                    Spin sp;
                    const int plast = (p + 1) * TPP - NPLAIN * NST;
                    const int target = min(plast + MARGIN, NDYN - TAILPOLL);
                    while (desc[9] < target) { __nanosleep(250); sp.tick(); }
                    if (b == NB - 1) collect_o(g < NB - 1);
                    while (true) {
                        e = ld_relaxed2(mlp);
                        const uint32_t miss = __ballot_sync(~0u, ((e.x ^ tag) | (e.y ^ tag)) & 1u);
                        if (!miss) break;
                        __nanosleep(miss == ~0u ? 300 : 20);
                        sp.tick();
                    }
                }
#pragma unroll
                for (int i = 0; i < 4; i++) v[i] = ld_relaxed4(rows + i * 64);
                const float m = untagf(e.x);
                float M = m;
#pragma unroll
                for (int o = 16; o; o >>= 1) M = fmaxf(M, __shfl_xor_sync(~0u, M, o));
                const float w = ex2(m - M) * untagf(e.y);
                float L = w;
#pragma unroll
                for (int o = 16; o; o >>= 1) L += __shfl_xor_sync(~0u, L, o);
                float wr[4];
#pragma unroll
                for (int i = 0; i < 4; i++) wr[i] = __shfl_sync(~0u, w, i * 8 + g);
                {
                    Spin sp;
                    while (__any_sync(~0u, bad4(v[0], tag) | bad4(v[1], tag) | bad4(v[2], tag) | bad4(v[3], tag))) {
#pragma unroll
                        for (int i = 0; i < 4; i++) v[i] = ld_relaxed4(rows + i * 64);
                        sp.tick();
                    }
                }
                float acc[8];
#pragma unroll
                for (int k = 0; k < 8; k++) acc[k] = 0.f;
#pragma unroll
                for (int i = 0; i < 4; i++) {
                    const uint32_t u[4] = {v[i].x, v[i].y, v[i].z, v[i].w};
#pragma unroll
                    for (int k = 0; k < 4; k++) {
                        acc[2 * k] = fmaf(wr[i], __uint_as_float((u[k] << 16) & 0xFFFE0000u), acc[2 * k]);
                        acc[2 * k + 1] = fmaf(wr[i], __uint_as_float(u[k] & 0xFFFF0000u), acc[2 * k + 1]);
                    }
                }
#pragma unroll
                for (int k = 0; k < 8; k++) {
                    acc[k] += __shfl_xor_sync(~0u, acc[k], 4);
                    acc[k] += __shfl_xor_sync(~0u, acc[k], 8);
                    acc[k] += __shfl_xor_sync(~0u, acc[k], 16);
                }
                float* part = reinterpret_cast<float*>(sg + SM_PART) + (b & 1) * 160;
                if (g == 0) {
#pragma unroll
                    for (int k = 0; k < 4; k++) *reinterpret_cast<float2*>(part + cw * 40 + k * 8 + 2 * t) = make_float2(acc[k], acc[k + 4]);
                    if (t == 0) *reinterpret_cast<float2*>(part + cw * 40 + 32) = make_float2(M, L);
                }
                bar_comb();
                if (ctid < 8) {
                    float2 ml4[4];
#pragma unroll
                    for (int i = 0; i < 4; i++) ml4[i] = *reinterpret_cast<const float2*>(part + i * 40 + 32);
                    const float MM = fmaxf(fmaxf(ml4[0].x, ml4[1].x), fmaxf(ml4[2].x, ml4[3].x));
                    float sw[4], LL = 0.f;
#pragma unroll
                    for (int i = 0; i < 4; i++) { sw[i] = ex2(ml4[i].x - MM); LL = fmaf(sw[i], ml4[i].y, LL); }
                    const float inv = 1.0f / LL;
                    uint32_t pk[2];
#pragma unroll
                    for (int j = 0; j < 2; j++) {
                        float o0 = 0.f, o1 = 0.f;
#pragma unroll
                        for (int i = 0; i < 4; i++) {
                            const float2 pv = *reinterpret_cast<const float2*>(part + i * 40 + g * 16 + j * 8 + 2 * t);
                            o0 = fmaf(sw[i], pv.x, o0); o1 = fmaf(sw[i], pv.y, o1);
                        }
                        pk[j] = pack_bf16(o0 * inv, o1 * inv);
                    }
                    uint4* dst = g_ox + (cta * NB + b) * 8 + ctid;
                    st_relaxed4(dst, (pk[0] << 16) | tag, (pk[0] & 0xFFFF0000u) | tag, (pk[1] << 16) | tag, (pk[1] & 0xFFFF0000u) | tag);
                    if (b == NB - 2) st_relaxed4(dst + 8, tag ^ 1u, tag ^ 1u, tag ^ 1u, tag ^ 1u);
                }
                if (b == NB - 2) {
                    const uint32_t inv = tag ^ 1u;
                    put_tile(sdst, inv, inv, inv, inv, true);
                    if (cw == 0) put_tile(sdst + 64, inv, inv, inv, inv, false);
                }
                __syncwarp();
            }
            {
                __nanosleep(ODELAY);
                const int m4 = lane >> 3;
                const uint32_t a0 = sb + SM_WBUF + ((m4 >> 1) * 8 + (lane & 7)) * 144 + (m4 & 1) * 16;
                uint32_t a[16][4], a2[4][4];
                auto load_a = [&]() {
#pragma unroll
                    for (int ks = 0; ks < 16; ks++) ldsm4t(a[ks], a0 + ks * (16 * 144) + cw * 32);
#pragma unroll
                    for (int i = 0; i < 4; i++) ldsm4t(a2[i], a0 + (cw * 4 + i) * (16 * 144) + 128);
                };
                bool have_a = false;
                const uint4* src = g_ox + ((hkv * 8 + (lane >> 3)) * NB + NB - 1) * 8 + (lane & 7);
                uint4 v0, v1;
                Spin sp;
                while (true) {
                    v0 = ld_relaxed4(src); v1 = ld_relaxed4(src + 4 * NB * 8);
                    if (!have_a && __all_sync(~0u, mbar_test(bar_wo + (lane & 3) * 8, 0))) { __syncwarp(); load_a(); have_a = true; }
                    if (!__any_sync(~0u, bad4(v0, tag) | bad4(v1, tag))) break;
                    sp.tick();
                }
                {
                    uint4* ox = reinterpret_cast<uint4*>(sg + SM_OB) + cw * 32;
                    ox[(lane & 3) * 8 + (lane >> 2)] = make_uint4(__byte_perm(v0.x, v0.y, 0x7632), __byte_perm(v0.z, v0.w, 0x7632),
                                                                  __byte_perm(v1.x, v1.y, 0x7632), __byte_perm(v1.z, v1.w, 0x7632));
                    __syncwarp();
                    if (g == NB - 1) {
#pragma unroll
                        for (int i = 0; i < 8; i++) { const uint4 w4 = ox[t * 8 + i]; ob[i][0] = w4.x; ob[i][1] = w4.y; ob[8 + i][0] = w4.z; ob[8 + i][1] = w4.w; }
                    }
                }
                float c0[4] = {0.f, 0.f, 0.f, 0.f}, c1[4] = {0.f, 0.f, 0.f, 0.f}, c2[4] = {0.f, 0.f, 0.f, 0.f};
                uint32_t b2[4][2];
#pragma unroll
                for (int i = 0; i < 4; i++) {
                    b2[i][0] = cw == 0 ? ob[i][0] : cw == 1 ? ob[4 + i][0] : cw == 2 ? ob[8 + i][0] : ob[12 + i][0];
                    b2[i][1] = cw == 0 ? ob[i][1] : cw == 1 ? ob[4 + i][1] : cw == 2 ? ob[8 + i][1] : ob[12 + i][1];
                }
                if (have_a) {
#pragma unroll
                    for (int i = 0; i < 4; i++) mma16816(c2, a2[i], b2[i][0], b2[i][1]);
#pragma unroll
                    for (int ks = 0; ks < 16; ks++) mma16816((ks & 1) ? c1 : c0, a[ks], ob[ks][0], ob[ks][1]);
                } else {
#pragma unroll
                    for (int pc = 0; pc < 4; pc++) {
                        mbar_wait(bar_wo + pc * 8, 0);
#pragma unroll
                        for (int i = 0; i < 4; i++) ldsm4t(a[i], a0 + (pc * 4 + i) * (16 * 144) + cw * 32);
                        if (pc == cw) {
#pragma unroll
                            for (int i = 0; i < 4; i++) ldsm4t(a2[i], a0 + (pc * 4 + i) * (16 * 144) + 128);
#pragma unroll
                            for (int i = 0; i < 4; i++) mma16816(c2, a2[i], b2[i][0], b2[i][1]);
                        }
#pragma unroll
                        for (int i = 0; i < 4; i++) mma16816((i & 1) ? c1 : c0, a[i], ob[pc * 4 + i][0], ob[pc * 4 + i][1]);
                    }
                }
                float2* x4 = reinterpret_cast<float2*>(sg + SM_PART);
                x4[cw * 32 + lane] = make_float2(c2[0], c2[1]);
                put_tile(sdst, tagf(c0[0] + c1[0], tag), tagf(c0[1] + c1[1], tag), tagf(c0[2] + c1[2], tag), tagf(c0[3] + c1[3], tag), true);
                bar_comb();
                if (cw == 0) {
                    const float2 p0 = x4[lane], p1 = x4[32 + lane], p2 = x4[64 + lane], p3 = x4[96 + lane];
                    put_tile(sdst + 64, tagf((p0.x + p1.x) + (p2.x + p3.x), tag), tagf((p0.y + p1.y) + (p2.y + p3.y), tag), 0, 0, false);
                }
            }
            gather16(g_sp + cta * 36, reinterpret_cast<float*>(sg + SM_RED) + 144, ctid, tag);
            __syncwarp();
            if (lane == 0) mbar_arrive(bar_ssum);
        }
    }
}

#define f_q (reinterpret_cast<float*>(g_po))
#define f_o (f_q + NB * 4096)
#define f_h (f_o + NB * 4096)

__global__ void fb_proj(const __nv_bfloat16* x, const __nv_bfloat16* wq, const __nv_bfloat16* wg, const __nv_bfloat16* wu) {
    __shared__ float xn[DM];
    const int b = blockIdx.y, n = blockIdx.x * blockDim.x + threadIdx.x;
    float s = 0.f, q = 0.f;
    for (int i = 0; i < DM; i++) s += __bfloat162float(x[b * DM + i]);
    const float mean = s / DM;
    for (int i = 0; i < DM; i++) { const float d = __bfloat162float(x[b * DM + i]) - mean; q += d * d; }
    const float den = bfr(sqrtf(bfr(bfr(q / DM) + 1e-5f)));
    for (int i = threadIdx.x; i < DM; i += blockDim.x) xn[i] = bfr(bfr(__bfloat162float(x[b * DM + i]) - bfr(mean)) / den);
    __syncthreads();
    if (n < 4096) {
        float a = 0.f;
        for (int k = 0; k < DM; k++) a += xn[k] * __bfloat162float(wq[(size_t)k * 4096 + n]);
        f_q[b * 4096 + n] = bfr(a);
    }
    if (n < FF) {
        float g = 0.f, u = 0.f;
        for (int k = 0; k < DM; k++) { g += xn[k] * __bfloat162float(wg[(size_t)k * FF + n]); u += xn[k] * __bfloat162float(wu[(size_t)k * FF + n]); }
        f_h[b * FF + n] = bfr(bfr(silu_f(bfr(g))) * bfr(u));
    }
}
__global__ void fb_attn(const __nv_bfloat16* K, const __nv_bfloat16* V) {
    __shared__ float sc[SK], red[128];
    const int t = threadIdx.x, b = blockIdx.x >> 5, h = blockIdx.x & 31;
    const __nv_bfloat16* k = K + (size_t)(b * HKV + (h >> 1)) * SK * 128;
    const __nv_bfloat16* v = V + (size_t)(b * HKV + (h >> 1)) * SK * 128;
    const float* q = f_q + b * 4096 + h * 128;
    float m = -INFINITY, l = 0.f, o = 0.f;
    for (int j = t; j < SK; j += 128) {
        float s = 0.f;
        for (int d = 0; d < 128; d++) s += q[d] * __bfloat162float(k[(size_t)j * 128 + d]);
        sc[j] = bfr(bfr(s) * 0.08838834764831845f); m = fmaxf(m, sc[j]);
    }
    red[t] = m; __syncthreads();
    for (int i = 0; i < 128; i++) m = fmaxf(m, red[i]);
    __syncthreads();
    for (int j = t; j < SK; j += 128) { sc[j] = __expf(sc[j] - m); l += sc[j]; }
    red[t] = l; __syncthreads();
    l = 0.f;
    for (int i = 0; i < 128; i++) l += red[i];
    for (int j = 0; j < SK; j++) o += sc[j] * __bfloat162float(v[(size_t)j * 128 + t]);
    f_o[b * 4096 + h * 128 + t] = bfr(o / l);
}
__global__ void fb_out(const __nv_bfloat16* x, const __nv_bfloat16* wo, const __nv_bfloat16* wd, __nv_bfloat16* out) {
    const int b = blockIdx.y, n = blockIdx.x * blockDim.x + threadIdx.x;
    float s = 0.f, f = 0.f;
    for (int k = 0; k < 4096; k++) s += f_o[b * 4096 + k] * __bfloat162float(wo[(size_t)k * DM + n]);
    for (int k = 0; k < FF; k++) f += f_h[b * FF + k] * __bfloat162float(wd[(size_t)k * DM + n]);
    out[b * DM + n] = __float2bfloat16_rn(__bfloat162float(x[b * DM + n]) + bfr(bfr(s) * bfr(silu_f(bfr(f)))));
}

typedef CUresult (*EncodeFn)(CUtensorMap*, CUtensorMapDataType, cuuint32_t, void*, const cuuint64_t*, const cuuint64_t*,
                             const cuuint32_t*, const cuuint32_t*, CUtensorMapInterleave, CUtensorMapSwizzle,
                             CUtensorMapL2promotion, CUtensorMapFloatOOBfill);

void make_map(EncodeFn enc, CUtensorMap* m, const void* p, int rank, const cuuint64_t* dims, const cuuint64_t* strides,
              const cuuint32_t* box, CUtensorMapSwizzle sw, CUtensorMapL2promotion promo) {
    cuuint32_t es[3] = {1, 1, 1};
    enc(m, CU_TENSOR_MAP_DATA_TYPE_BFLOAT16, rank, const_cast<void*>(p), dims, strides, box, es,
        CU_TENSOR_MAP_INTERLEAVE_NONE, sw, promo, CU_TENSOR_MAP_FLOAT_OOB_FILL_NONE);
}

}

extern "C" void kernel_launch(void* const* d_in, const int* in_sizes, int n_in, void* d_out, int out_size) {
    (void)in_sizes; (void)n_in; (void)out_size;
    static EncodeFn enc = nullptr;
    static int mode = 0;
    if (!mode) {
        void* fn = nullptr;
        cudaDriverEntryPointQueryResult qr;
        cudaGetDriverEntryPoint("cuTensorMapEncodeTiled", &fn, cudaEnableDefault, &qr);
        enc = (EncodeFn)fn;
        int dev = 0, sms = 0, occ = 0;
        cudaGetDevice(&dev);
        cudaDeviceGetAttribute(&sms, cudaDevAttrMultiProcessorCount, dev);
        cudaFuncSetAttribute(fused_decode_kernel, cudaFuncAttributeMaxDynamicSharedMemorySize, SMEM_BYTES);
        cudaOccupancyMaxActiveBlocksPerMultiprocessor(&occ, fused_decode_kernel, NTHREADS, SMEM_BYTES);
        mode = (enc && occ * sms >= NCTA) ? 1 : 2;
    }
    typedef const __nv_bfloat16* P;
    if (mode == 2) {
        fb_proj<<<dim3(FF / 128, NB), 128>>>((P)d_in[0], (P)d_in[3], (P)d_in[6], (P)d_in[7]);
        fb_attn<<<NB * 32, 128>>>((P)d_in[1], (P)d_in[2]);
        fb_out<<<dim3(DM / 64, NB), 64>>>((P)d_in[0], (P)d_in[4], (P)d_in[8], (__nv_bfloat16*)d_out);
        return;
    }
    Maps maps;
    const cuuint64_t kvrows = (cuuint64_t)NPAIR * SK;
    for (int i = 0; i < 2; i++) {
        cuuint64_t dims[3] = {64, kvrows, 2}, strides[2] = {256, 128};
        cuuint32_t box[3] = {64, TILE, 2};
        make_map(enc, i ? &maps.v : &maps.k, d_in[1 + i], 3, dims, strides, box, CU_TENSOR_MAP_SWIZZLE_128B, CU_TENSOR_MAP_L2_PROMOTION_L2_256B);
    }
    {
        cuuint32_t box[2] = {32, 192};
        cuuint64_t dq[2] = {4096, DM}, sq[1] = {4096 * 2};
        make_map(enc, &maps.wq, d_in[3], 2, dq, sq, box, CU_TENSOR_MAP_SWIZZLE_64B, CU_TENSOR_MAP_L2_PROMOTION_L2_128B);
        cuuint64_t df[2] = {FF, DM}, sf[1] = {FF * 2};
        make_map(enc, &maps.wg, d_in[6], 2, df, sf, box, CU_TENSOR_MAP_SWIZZLE_64B, CU_TENSOR_MAP_L2_PROMOTION_L2_128B);
        make_map(enc, &maps.wu, d_in[7], 2, df, sf, box, CU_TENSOR_MAP_SWIZZLE_64B, CU_TENSOR_MAP_L2_PROMOTION_L2_128B);
    }
    {
        cuuint32_t boxo[2] = {72, 64};
        cuuint64_t d_o[2] = {DM, 4096}, s_o[1] = {DM * 2};
        make_map(enc, &maps.wo, d_in[4], 2, d_o, s_o, boxo, CU_TENSOR_MAP_SWIZZLE_NONE, CU_TENSOR_MAP_L2_PROMOTION_L2_128B);
        cuuint32_t boxd[2] = {64, 96};
        cuuint64_t d_d[2] = {DM, FF}, s_d[1] = {DM * 2};
        make_map(enc, &maps.wd, d_in[8], 2, d_d, s_d, boxd, CU_TENSOR_MAP_SWIZZLE_128B, CU_TENSOR_MAP_L2_PROMOTION_L2_128B);
    }
    fused_decode_kernel<<<NCTA, NTHREADS, SMEM_BYTES>>>(maps, (const __nv_bfloat16*)d_in[0], (__nv_bfloat16*)d_out);
}
```
